```python
import torch

def _softmax(x, axis=-1):
    return torch.softmax(x, dim=axis)
def _gelu(x):
    return torch.nn.functional.gelu(x, approximate="tanh")
def _silu(x):
    return torch.nn.functional.silu(x)
def _sigmoid(x):
    return torch.sigmoid(x)
def _layernorm(x, axis=-1, eps=1e-5):
    m = x.mean(dim=axis, keepdim=True)
    v = x.var(dim=axis, keepdim=True, unbiased=False)
    return (x - m) / torch.sqrt(v + eps)
def _scatter_add(tgt, idx, src, axis=0):
    return tgt.clone().index_add_(axis, idx, src)
def _segment_sum(src, seg, n):
    out = torch.zeros((n,) + src.shape[1:], dtype=src.dtype)
    return out.index_add_(0, seg, src)
def _pad(x, pw):
    flat = tuple(v for pair in reversed(pw) for v in pair)
    return torch.nn.functional.pad(x, flat)

kernel_name = 'parallel_sum__sliding_block_cached__dense_activation_silu__decode'

def setup_inputs():

    _w = (lambda a: (lambda t: t.to(torch.bfloat16) if t.is_floating_point() else t)(torch.as_tensor(a)))
    def _A_setup():
        B, Sq, D = 8, 1, 512
        Hq, Hkv, Sk, Dh = 32, 8, 4096, 128
        assert Hq % Hkv == 0, (Hq, Hkv)
        return {
            "x": _w((lambda *s: torch.randn(*s, dtype=torch.bfloat16) * 0.05)(B, Sq, D)),
            "k_cache": _w((lambda *s: torch.randn(*s, dtype=torch.bfloat16) * 3.2)(B, Hkv, Sk, Dh)),
            "v_cache": _w((lambda *s: torch.randn(*s, dtype=torch.bfloat16) * 0.8)(B, Hkv, Sk, Dh)),
            "wq": _w((lambda *s: torch.randn(*s, dtype=torch.bfloat16) * 3.2)(D, Hq * Dh) * (D ** -0.5)),
            "wo": _w((lambda *s: torch.randn(*s, dtype=torch.bfloat16) * 0.8)(Hq * Dh, D) * ((Hq * Dh) ** -0.5)),
        }
    _A_in = _A_setup()

    def _B_setup():
        B, S, D, F = 8, 1, 512, 1792
        return {
            "x": _w((lambda *s: torch.randn(*s, dtype=torch.bfloat16) * 0.05)(B, S, D)),
            "w1": _w((lambda *s: torch.randn(*s, dtype=torch.bfloat16) * 3.2)(D, F) * (D ** -0.5)),
            "w2": _w((lambda *s: torch.randn(*s, dtype=torch.bfloat16) * 0.4)(F, D) * (F ** -0.5)),
        }
    _B_in = _B_setup()

    return {
        "A_x": _A_in["x"],
        "A_k_cache": _A_in["k_cache"],
        "A_v_cache": _A_in["v_cache"],
        "A_wq": _A_in["wq"],
        "A_wo": _A_in["wo"],
        "B_x": _B_in["x"],
        "B_w1": _B_in["w1"],
        "B_w2": _B_in["w2"],
    }

def reference(A_x, A_k_cache, A_v_cache, A_wq, A_wo, B_x, B_w1, B_w2):
    def _A_ref(x, k_cache, v_cache, wq, wo):
        B, Sq, D = x.shape
        Hq, Dh = 32, 128
        Hkv, Sk = k_cache.shape[1], k_cache.shape[2]
        W = min(4096, max(256, Sk // 4))
        rep = Hq // Hkv
        q = (lambda x, *d: x.permute(*d))((x @ wq).reshape(B, Sq, Hq, Dh), 0, 2, 1, 3)
        k = (lambda x, n, axis: torch.repeat_interleave(x, n, dim=axis))(k_cache[:, :, Sk - W:, :], rep, axis=1)
        v = (lambda x, n, axis: torch.repeat_interleave(x, n, dim=axis))(v_cache[:, :, Sk - W:, :], rep, axis=1)
        scores = torch.einsum("bhqd,bhkd->bhqk", q, k) * (Dh ** -0.5)
        p = _softmax(scores, axis=-1)
        o = torch.einsum("bhqk,bhkd->bhqd", p, v)
        return (lambda x, *d: x.permute(*d))(o, 0, 2, 1, 3).reshape(B, Sq, Hq * Dh) @ wo

    def _B_ref(x, w1, w2):
        h = torch.einsum("bsd,df->bsf", x, w1)
        h = _silu(h)
        out = torch.einsum("bsf,fd->bsd", h, w2)
        return out

    x = A_x
    xn = _layernorm(x, axis=-1)
    return x + _A_ref(xn, A_k_cache, A_v_cache, A_wq, A_wo) + _B_ref(xn, B_w1, B_w2)
```

```cpp
#include <cuda_runtime.h>
#include <cuda_bf16.h>
#include <cuda.h>
#include <stdint.h>

namespace {

constexpr int NCTA = 128;
constexpr int NTHREADS = 288;
constexpr int CHUNK = 16384;
constexpr int NSLOT = 12;
constexpr int NCHUNK = 22;
constexpr int DEPTH = 4;
constexpr uint32_t SPIN_LIMIT = 1u << 24;

constexpr int XN_PITCH = 1040;
constexpr int RED_PITCH = 52;
constexpr int OFF_RING = 0;
constexpr int OFF_XN = NSLOT * CHUNK;
constexpr int OFF_P = OFF_XN + 8320;
constexpr int OFF_RED = OFF_P + 8192;
constexpr int OFF_STAT = OFF_RED + 13312;
constexpr int OFF_BAR = OFF_STAT + 512;
constexpr int SMEM_USED = OFF_BAR + 32 * 8;
constexpr int SMEM_BYTES = SMEM_USED + 1024;

struct Maps { CUtensorMap k, v, wq, w1, wo, w2; };

__device__ unsigned int g_epoch;
__device__ unsigned int g_flag[NCTA];
__device__ __align__(128) uint32_t g_q[8 * 2048];
__device__ __align__(128) uint32_t g_h[8 * 896];
__device__ __align__(128) uint32_t g_ml[NCTA * 8];
__device__ __align__(128) uint32_t g_o[2 * 8 * 2048];
__device__ __align__(128) uint32_t g_part[NCTA * 256];

#define TSTAMP(idx) do { } while (0)

__device__ __forceinline__ uint32_t smem_u32(const void* p) { return (uint32_t)__cvta_generic_to_shared(p); }
__device__ __forceinline__ void mbar_init(uint32_t bar, uint32_t cnt) {
    asm volatile("mbarrier.init.shared::cta.b64 [%0], %1;" :: "r"(bar), "r"(cnt) : "memory");
}
__device__ __forceinline__ void mbar_expect(uint32_t bar, uint32_t bytes) {
    asm volatile("mbarrier.arrive.expect_tx.shared::cta.b64 _, [%0], %1;" :: "r"(bar), "r"(bytes) : "memory");
}
__device__ __forceinline__ void mbar_arrive(uint32_t bar) {
    asm volatile("mbarrier.arrive.shared::cta.b64 _, [%0];" :: "r"(bar) : "memory");
}
__device__ __forceinline__ void mbar_wait(uint32_t bar) {
    uint32_t done;
    for (uint32_t it = 0; ; ++it) {
        asm volatile("{\n.reg .pred p;\nmbarrier.try_wait.parity.shared::cta.b64 p, [%1], 0;\nselp.u32 %0, 1, 0, p;\n}"
                     : "=r"(done) : "r"(bar) : "memory");
        if (done) break;
        if (it > SPIN_LIMIT) __trap();
    }
}
__device__ __forceinline__ void tma2d(uint32_t dst, const CUtensorMap* m, int c0, int c1, uint32_t bar) {
    asm volatile("cp.async.bulk.tensor.2d.shared::cluster.global.mbarrier::complete_tx::bytes [%0], [%1, {%3, %4}], [%2];"
                 :: "r"(dst), "l"(m), "r"(bar), "r"(c0), "r"(c1) : "memory");
}
__device__ __forceinline__ void tma3d(uint32_t dst, const CUtensorMap* m, int c0, int c1, int c2, uint32_t bar) {
    asm volatile("cp.async.bulk.tensor.3d.shared::cluster.global.mbarrier::complete_tx::bytes [%0], [%1, {%3, %4, %5}], [%2];"
                 :: "r"(dst), "l"(m), "r"(bar), "r"(c0), "r"(c1), "r"(c2) : "memory");
}
__device__ __forceinline__ void l2_prefetch(const void* src, uint32_t bytes) {
    asm volatile("cp.async.bulk.prefetch.L2.global [%0], %1;" :: "l"(src), "r"(bytes) : "memory");
}
__device__ __forceinline__ void ldsm4(uint32_t (&r)[4], uint32_t addr) {
    asm volatile("ldmatrix.sync.aligned.m8n8.x4.shared.b16 {%0,%1,%2,%3}, [%4];"
                 : "=r"(r[0]), "=r"(r[1]), "=r"(r[2]), "=r"(r[3]) : "r"(addr) : "memory");
}
__device__ __forceinline__ void ldsm4t(uint32_t (&r)[4], uint32_t addr) {
    asm volatile("ldmatrix.sync.aligned.m8n8.x4.trans.shared.b16 {%0,%1,%2,%3}, [%4];"
                 : "=r"(r[0]), "=r"(r[1]), "=r"(r[2]), "=r"(r[3]) : "r"(addr) : "memory");
}
__device__ __forceinline__ void mma16816(float (&d)[4], const uint32_t (&a)[4], uint32_t b0, uint32_t b1) {
    asm volatile("mma.sync.aligned.m16n8k16.row.col.f32.bf16.bf16.f32 {%0,%1,%2,%3}, {%4,%5,%6,%7}, {%8,%9}, {%0,%1,%2,%3};"
                 : "+f"(d[0]), "+f"(d[1]), "+f"(d[2]), "+f"(d[3])
                 : "r"(a[0]), "r"(a[1]), "r"(a[2]), "r"(a[3]), "r"(b0), "r"(b1));
}
__device__ __forceinline__ uint32_t movtrans(uint32_t a) {
    uint32_t d;
    asm volatile("movmatrix.sync.aligned.m8n8.trans.b16 %0, %1;" : "=r"(d) : "r"(a));
    return d;
}
__device__ __forceinline__ uint32_t pack_bf16(float lo, float hi) {
    uint32_t d;
    asm("cvt.rn.bf16x2.f32 %0, %1, %2;" : "=r"(d) : "f"(hi), "f"(lo));
    return d;
}
__device__ __forceinline__ float bf16r(float x) { return __bfloat162float(__float2bfloat16_rn(x)); }
__device__ __forceinline__ float bf_lo(uint32_t u) { return __uint_as_float(u << 16); }
__device__ __forceinline__ float bf_hi(uint32_t u) { return __uint_as_float(u & 0xffff0000u); }
__device__ __forceinline__ uint32_t nz(uint32_t v) { return v == 0u ? 0x80000000u : v; }
__device__ __forceinline__ uint32_t hadd2_bf16(uint32_t a, uint32_t b) {
    uint32_t d;
    asm("add.rn.bf16x2 %0, %1, %2;" : "=r"(d) : "r"(a), "r"(b));
    return d;
}
__device__ __forceinline__ uint32_t ld_rlx(const uint32_t* p) {
    uint32_t v; asm volatile("ld.relaxed.gpu.global.u32 %0, [%1];" : "=r"(v) : "l"(p) : "memory"); return v;
}
__device__ __forceinline__ uint32_t ld_acq(const uint32_t* p) {
    uint32_t v; asm volatile("ld.acquire.gpu.global.u32 %0, [%1];" : "=r"(v) : "l"(p) : "memory"); return v;
}
__device__ __forceinline__ uint2 ld_rlx2(const uint32_t* p) {
    uint2 v; asm volatile("ld.relaxed.gpu.global.v2.u32 {%0,%1}, [%2];" : "=r"(v.x), "=r"(v.y) : "l"(p) : "memory"); return v;
}
__device__ __forceinline__ void st_rlx(uint32_t* p, uint32_t v) {
    asm volatile("st.relaxed.gpu.global.u32 [%0], %1;" :: "l"(p), "r"(v) : "memory");
}
__device__ __forceinline__ void st_rlx2(uint32_t* p, uint32_t a, uint32_t b) {
    asm volatile("st.relaxed.gpu.global.v2.u32 [%0], {%1,%2};" :: "l"(p), "r"(a), "r"(b) : "memory");
}
__device__ __forceinline__ void st_rel(uint32_t* p, uint32_t v) {
    asm volatile("st.release.gpu.global.u32 [%0], %1;" :: "l"(p), "r"(v) : "memory");
}
__device__ __forceinline__ void cbar() { asm volatile("bar.sync 1, 256;" ::: "memory"); }
__device__ __forceinline__ float ex2(float x) { float y; asm("ex2.approx.ftz.f32 %0, %1;" : "=f"(y) : "f"(x)); return y; }

__global__ void __launch_bounds__(NTHREADS, 1)
fused_decode_kernel(const __grid_constant__ Maps maps, const __nv_bfloat16* __restrict__ x,
                    const char* __restrict__ wq_raw, __nv_bfloat16* __restrict__ out)
{
    extern __shared__ char smem_raw[];
    const uint32_t sm = (smem_u32(smem_raw) + 1023u) & ~1023u;
    char* smp = smem_raw + (sm - smem_u32(smem_raw));
    const int tid = threadIdx.x, warp = tid >> 5, lane = tid & 31;
    const int cta = blockIdx.x, g = cta >> 4, c = cta & 15, b = c >> 1, half = c & 1;
    const uint32_t bar_full = sm + OFF_BAR, bar_empty = bar_full + NCHUNK * 8;

    if (warp == 8) {
        if (lane == 0) {
            TSTAMP(0);
            l2_prefetch(wq_raw + (size_t)cta * 32768, 16384);
            for (int s = 0; s < NCHUNK; s++) mbar_init(bar_full + s * 8, 1);
            mbar_init(bar_empty, 8);
            for (int s = 1; s < 8; s++) mbar_init(bar_empty + s * 8, 1);
            asm volatile("fence.mbarrier_init.release.cluster;" ::: "memory");
            asm volatile("fence.proxy.async.shared::cta;" ::: "memory");
        }
        const int row0 = (b * 8 + g) * 4096 + 3072 + half * 512;
        auto issue = [&](int ch) {
            const uint32_t dst = sm + OFF_RING + (ch % NSLOT) * CHUNK, bar = bar_full + ch * 8;
            if (ch < 2) { mbar_expect(bar, CHUNK); tma2d(dst, &maps.wq, cta * 32, ch * 256, bar); }
            else if (ch == 2) {
                if (c < 14) {
                    mbar_expect(bar, CHUNK);
                    tma2d(dst, &maps.w1, g * 224 + c * 16, 0, bar);
                    tma2d(dst + 8192, &maps.w1, g * 224 + c * 16, 256, bar);
                } else mbar_arrive(bar);
            }
            else if (ch < 11) { mbar_expect(bar, CHUNK); tma3d(dst, &maps.k, 0, row0 + (ch - 3) * 64, 0, bar); }
            else if (ch < 19) { mbar_expect(bar, CHUNK); tma3d(dst, &maps.v, 0, row0 + (ch - 11) * 64, 0, bar); }
            else if (ch < 21) { mbar_expect(bar, CHUNK); tma2d(dst, &maps.wo, c * 32, g * 512 + (ch - 19) * 256, bar); }
            else { mbar_expect(bar, 14336); tma2d(dst, &maps.w2, c * 32, g * 224, bar); }
        };
        if (lane == 0) {
            #pragma unroll
            for (int ch = 0; ch < DEPTH; ch++) issue(ch);
        }
        __syncthreads();
        if (lane == 0) {
            #pragma unroll
            for (int ch = DEPTH; ch < NCHUNK; ch++) {
                mbar_wait(bar_full + (ch - DEPTH) * 8);
                if (ch == NSLOT) mbar_wait(bar_empty);
                if (ch >= NSLOT + 3) mbar_wait(bar_empty + (ch - NSLOT - 2) * 8);
                issue(ch);
            }
        }
        return;
    }

    const int gl = lane >> 2, t = lane & 3;
    const uint32_t tag = ld_rlx(&g_epoch) + 1u;
    const uint4* xr = reinterpret_cast<const uint4*>(x + warp * 512) + lane * 2;
    const uint4 xa = __ldg(xr), xb = __ldg(xr + 1);
    float resid = 0.f;
    if (warp == g) resid = __bfloat162float(x[g * 512 + c * 32 + lane]);
    {
        const uint4 z = make_uint4(0, 0, 0, 0);
        if (tid < 64) reinterpret_cast<uint4*>(g_o + (half * 8 + b) * 2048 + g * 256)[tid] = z;
        else if (tid < 128) reinterpret_cast<uint4*>(g_part + cta * 256)[tid - 64] = z;
        else if (tid < 130) reinterpret_cast<uint4*>(g_ml + cta * 8)[tid - 128] = z;
    }
    {
        float v[16];
        const uint32_t w[8] = {xa.x, xa.y, xa.z, xa.w, xb.x, xb.y, xb.z, xb.w};
        #pragma unroll
        for (int j = 0; j < 8; j++) { v[2 * j] = bf_lo(w[j]); v[2 * j + 1] = bf_hi(w[j]); }
        float s = 0.f;
        #pragma unroll
        for (int j = 0; j < 16; j++) s += v[j];
        #pragma unroll
        for (int o = 16; o > 0; o >>= 1) s += __shfl_xor_sync(0xffffffffu, s, o);
        const float mean = s * (1.f / 512.f);
        float q2 = 0.f;
        #pragma unroll
        for (int j = 0; j < 16; j++) { const float d = v[j] - mean; q2 += d * d; }
        #pragma unroll
        for (int o = 16; o > 0; o >>= 1) q2 += __shfl_xor_sync(0xffffffffu, q2, o);
        const float mb = bf16r(mean);
        const float den = bf16r(__fsqrt_rn(bf16r(bf16r(q2 * (1.f / 512.f)) + 1e-5f)));
        uint32_t o8[8];
        #pragma unroll
        for (int j = 0; j < 8; j++)
            o8[j] = pack_bf16(__fdiv_rn(bf16r(v[2 * j] - mb), den), __fdiv_rn(bf16r(v[2 * j + 1] - mb), den));
        uint4* dst = reinterpret_cast<uint4*>(smp + OFF_XN + warp * XN_PITCH + lane * 32);
        dst[0] = make_uint4(o8[0], o8[1], o8[2], o8[3]);
        dst[1] = make_uint4(o8[4], o8[5], o8[6], o8[7]);
    }
    __syncthreads();
    if (tid == 0) TSTAMP(1);

    float* red = reinterpret_cast<float*>(smp + OFF_RED);
    const int mj = lane >> 3, mr = lane & 7;
    {
        uint32_t xb4[2][4];
        #pragma unroll
        for (int i = 0; i < 2; i++)
            ldsm4(xb4[i], sm + OFF_XN + mr * XN_PITCH + (warp * 64 + i * 32 + mj * 8) * 2);
        float aq[2][4] = {}, ah[4] = {};
        mbar_wait(bar_full + (warp >> 2) * 8);
        const uint32_t wqs = sm + OFF_RING + (warp >> 2) * CHUNK;
        #pragma unroll
        for (int s = 0; s < 4; s++) {
            const int row = (warp & 3) * 64 + s * 16 + (mj >> 1) * 8 + mr;
            #pragma unroll
            for (int j = 0; j < 2; j++) {
                uint32_t a[4];
                ldsm4t(a, wqs + row * 64 + (((2 * j + (mj & 1)) ^ ((row >> 1) & 3)) << 4));
                mma16816(aq[j], a, xb4[s >> 1][(s & 1) * 2], xb4[s >> 1][(s & 1) * 2 + 1]);
            }
        }
        if (c < 14) {
            mbar_wait(bar_full + 2 * 8);
            const uint32_t w1s = sm + OFF_RING + 2 * CHUNK;
            #pragma unroll
            for (int s = 0; s < 4; s++) {
                const int row = warp * 64 + s * 16 + (mj >> 1) * 8 + mr;
                uint32_t a[4];
                ldsm4t(a, w1s + row * 32 + (((mj & 1) ^ ((row >> 2) & 1)) << 4));
                mma16816(ah, a, xb4[s >> 1][(s & 1) * 2], xb4[s >> 1][(s & 1) * 2 + 1]);
            }
        }
        float* r0 = red + (warp * 8 + 2 * t) * RED_PITCH + gl;
        #pragma unroll
        for (int j = 0; j < 2; j++) {
            r0[j * 16] = aq[j][0]; r0[RED_PITCH + j * 16] = aq[j][1];
            r0[j * 16 + 8] = aq[j][2]; r0[RED_PITCH + j * 16 + 8] = aq[j][3];
        }
        r0[32] = ah[0]; r0[RED_PITCH + 32] = ah[1]; r0[40] = ah[2]; r0[RED_PITCH + 40] = ah[3];
        __syncwarp();
        if (lane == 0) mbar_arrive(bar_empty);
    }
    cbar();
    if (tid < 128) {
        const int bb = tid >> 4, wd = tid & 15;
        const int col = (wd >> 3) * 16 + ((wd >> 1) & 3) * 2 + (wd & 1) * 8;
        float s0 = 0.f, s1 = 0.f;
        #pragma unroll
        for (int w = 0; w < 8; w++) {
            const float2 f = *reinterpret_cast<const float2*>(red + (w * 8 + bb) * RED_PITCH + col);
            s0 += f.x; s1 += f.y;
        }
        g_q[bb * 2048 + cta * 16 + wd] = pack_bf16(s0, s1);
    } else if (tid < 192 && c < 14) {
        const int bb = (tid - 128) >> 3, wd = tid & 7;
        const int col = 32 + (wd >> 1) * 2 + (wd & 1) * 8;
        float s0 = 0.f, s1 = 0.f;
        #pragma unroll
        for (int w = 0; w < 8; w++) {
            const float2 f = *reinterpret_cast<const float2*>(red + (w * 8 + bb) * RED_PITCH + col);
            s0 += f.x; s1 += f.y;
        }
        s0 = bf16r(s0); s1 = bf16r(s1);
        s0 = __fdividef(s0, 1.f + __expf(-s0)); s1 = __fdividef(s1, 1.f + __expf(-s1));
        g_h[bb * 896 + (g * 14 + c) * 8 + wd] = pack_bf16(s0, s1);
    }
    cbar();
    if (tid == 0) { st_rel(&g_flag[cta], tag); TSTAMP(2); }

    {
        const bool on = lane < 16 || (warp == g && lane < 24);
        const uint32_t* fp = lane < 16 ? &g_flag[g * 16 + lane] : &g_flag[((lane - 16) & 7) * 16 + c];
        for (uint32_t it = 0; ; ++it) {
            const bool ok = !on || ld_acq(fp) == tag;
            if (__all_sync(0xffffffffu, ok)) break;
            if (it > SPIN_LIMIT) __trap();
        }
        __syncwarp();
    }
    if (tid == 0) TSTAMP(3);
    uint32_t hb[2][2] = {};
    float sc[4][4];
    {
        uint32_t qb[8][2];
        #pragma unroll
        for (int s = 0; s < 8; s++) {
            uint2 v = make_uint2(0u, 0u);
            if (gl < 4) v = ld_rlx2(g_q + b * 2048 + ((g * 4 + gl) * 8 + s) * 8 + t * 2);
            qb[s][0] = v.x; qb[s][1] = v.y;
        }
        if (warp < 7) {
            #pragma unroll
            for (int j = 0; j < 2; j++) {
                const uint2 v = ld_rlx2(g_h + gl * 896 + (g * 14 + warp * 2 + j) * 8 + t * 2);
                hb[j][0] = v.x; hb[j][1] = v.y;
            }
        }
        mbar_wait(bar_full + (3 + warp) * 8);
        const uint32_t ks = sm + OFF_RING + ((3 + warp) % NSLOT) * CHUNK;
        #pragma unroll
        for (int i = 0; i < 4; i++) { sc[i][0] = sc[i][1] = sc[i][2] = sc[i][3] = 0.f; }
        #pragma unroll
        for (int s = 0; s < 8; s++) {
            const int ch = 2 * s + (mj >> 1);
            #pragma unroll
            for (int i = 0; i < 4; i++) {
                const int row = i * 16 + (mj & 1) * 8 + mr;
                uint32_t a[4];
                ldsm4(a, ks + (ch >> 3) * 8192 + row * 128 + (((ch & 7) ^ mr) << 4));
                mma16816(sc[i], a, qb[s][0], qb[s][1]);
            }
        }
        __syncwarp();
        if (lane == 0 && warp < 7) mbar_arrive(bar_empty + (1 + warp) * 8);
    }
    float* wmax = reinterpret_cast<float*>(smp + OFF_STAT);
    float* wsum = wmax + 64;
    float m0, m1;
    {
        m0 = -INFINITY; m1 = -INFINITY;
        #pragma unroll
        for (int i = 0; i < 4; i++) {
            #pragma unroll
            for (int k = 0; k < 4; k++) sc[i][k] = bf16r(bf16r(sc[i][k]) * 0.08838834764831845f);
            m0 = fmaxf(m0, fmaxf(sc[i][0], sc[i][2]));
            m1 = fmaxf(m1, fmaxf(sc[i][1], sc[i][3]));
        }
        #pragma unroll
        for (int o = 4; o < 32; o <<= 1) {
            m0 = fmaxf(m0, __shfl_xor_sync(0xffffffffu, m0, o));
            m1 = fmaxf(m1, __shfl_xor_sync(0xffffffffu, m1, o));
        }
        if (lane < 4) *reinterpret_cast<float2*>(wmax + warp * 8 + 2 * lane) = make_float2(m0, m1);
        cbar();
        #pragma unroll
        for (int w = 0; w < 8; w++) {
            const float2 f = *reinterpret_cast<const float2*>(wmax + w * 8 + 2 * t);
            m0 = fmaxf(m0, f.x); m1 = fmaxf(m1, f.y);
        }
        constexpr float L2E = 1.4426950408889634f;
        float l0 = 0.f, l1 = 0.f;
        uint32_t pw[4][2];
        #pragma unroll
        for (int i = 0; i < 4; i++) {
            const float p0 = ex2((sc[i][0] - m0) * L2E), p1 = ex2((sc[i][1] - m1) * L2E);
            const float p2 = ex2((sc[i][2] - m0) * L2E), p3 = ex2((sc[i][3] - m1) * L2E);
            l0 += p0 + p2; l1 += p1 + p3;
            pw[i][0] = movtrans(pack_bf16(p0, p1));
            pw[i][1] = movtrans(pack_bf16(p2, p3));
        }
        uint4* pd = reinterpret_cast<uint4*>(smp + OFF_P) + (warp * 2) * 32 + lane;
        pd[0] = make_uint4(pw[0][0], pw[0][1], pw[1][0], pw[1][1]);
        pd[32] = make_uint4(pw[2][0], pw[2][1], pw[3][0], pw[3][1]);
        #pragma unroll
        for (int o = 4; o < 32; o <<= 1) {
            l0 += __shfl_xor_sync(0xffffffffu, l0, o);
            l1 += __shfl_xor_sync(0xffffffffu, l1, o);
        }
        if (lane < 4) *reinterpret_cast<float2*>(wsum + warp * 8 + 2 * lane) = make_float2(l0, l1);
    }
    cbar();
    float l0 = 0.f, l1 = 0.f;
    #pragma unroll
    for (int w = 0; w < 8; w++) {
        const float2 f = *reinterpret_cast<const float2*>(wsum + w * 8 + 2 * t);
        l0 += f.x; l1 += f.y;
    }
    if (warp == 0 && lane < 4) {
        const float la = __shfl_sync(0xfu, l0, lane & 1), lb = __shfl_sync(0xfu, l1, lane & 1);
        const float a = lane < 2 ? m0 : la, bq = lane < 2 ? m1 : lb;
        st_rlx2(g_ml + cta * 8 + lane * 2, nz(__float_as_uint(a)), nz(__float_as_uint(bq)));
    }
    if (tid == 0) TSTAMP(4);

    float f0, f1;
    float oc[4][4] = {};
    {
        uint4 pf[16];
        #pragma unroll
        for (int i = 0; i < 16; i++) pf[i] = reinterpret_cast<const uint4*>(smp + OFF_P)[i * 32 + lane];
        const int ch = 2 * warp + (mj & 1);
        const uint32_t voff = (ch >> 3) * 8192 + ((mj >> 1) * 8 + mr) * 128 + (((ch & 7) ^ mr) << 4);
        #pragma unroll
        for (int j = 0; j < 8; j++) {
            if (j == 5) {
                const uint32_t* pm = g_ml + (cta ^ 1) * 8 + (t & 1) * 2;
                uint2 mo, lo;
                for (uint32_t it = 0; ; ++it) {
                    mo = ld_rlx2(pm); lo = ld_rlx2(pm + 4);
                    if (mo.x && mo.y && lo.x && lo.y) break;
                    if (it > SPIN_LIMIT) __trap();
                }
                constexpr float L2E = 1.4426950408889634f;
                const float mo0 = __uint_as_float(mo.x), mo1 = __uint_as_float(mo.y);
                const float mt0 = fmaxf(m0, mo0), mt1 = fmaxf(m1, mo1);
                const float e0 = ex2((m0 - mt0) * L2E), e1 = ex2((m1 - mt1) * L2E);
                f0 = e0 / (l0 * e0 + __uint_as_float(lo.x) * ex2((mo0 - mt0) * L2E));
                f1 = e1 / (l1 * e1 + __uint_as_float(lo.y) * ex2((mo1 - mt1) * L2E));
                __syncwarp();
            }
            mbar_wait(bar_full + (11 + j) * 8);
            if (tid == 0) TSTAMP(8 + j);
            const uint32_t vs = sm + OFF_RING + ((11 + j) % NSLOT) * CHUNK + voff;
            #pragma unroll
            for (int s = 0; s < 4; s++) {
                uint32_t a[4];
                ldsm4t(a, vs + s * 2048);
                const uint4 p = pf[j * 2 + (s >> 1)];
                mma16816(oc[s], a, (s & 1) ? p.z : p.x, (s & 1) ? p.w : p.y);
            }
        }
    }
    {
        const float o0 = (oc[0][0] + oc[1][0]) + (oc[2][0] + oc[3][0]);
        const float o1 = (oc[0][1] + oc[1][1]) + (oc[2][1] + oc[3][1]);
        const float o2 = (oc[0][2] + oc[1][2]) + (oc[2][2] + oc[3][2]);
        const float o3 = (oc[0][3] + oc[1][3]) + (oc[2][3] + oc[3][3]);
        const uint32_t u0 = movtrans(pack_bf16(o0 * f0, o1 * f1));
        const uint32_t u1 = movtrans(pack_bf16(o2 * f0, o3 * f1));
        if (lane < 16)
            st_rlx2(g_o + (half * 8 + b) * 2048 + ((g * 4 + gl) * 8 + warp) * 8 + t * 2, nz(u0), nz(u1));
    }
    if (tid == 0) TSTAMP(16);

    {
        uint2 ov[8];
        const uint32_t* op = g_o + gl * 2048 + (g * 32 + warp * 4) * 8 + t * 2;
        #pragma unroll
        for (int k = 0; k < 8; k++) ov[k] = ld_rlx2(op + (k >> 2) * 16384 + (k & 3) * 8);
        for (uint32_t it = 0; ; ++it) {
            bool ok = true;
            #pragma unroll
            for (int k = 0; k < 8; k++) {
                if (ov[k].x == 0u || ov[k].y == 0u) { ov[k] = ld_rlx2(op + (k >> 2) * 16384 + (k & 3) * 8); ok = false; }
            }
            if (ok) break;
            if (it > SPIN_LIMIT) __trap();
        }
        __syncwarp();
        if (tid == 0) TSTAMP(17);
        float ac[2][4] = {}, af[2][4] = {};
        mbar_wait(bar_full + (19 + (warp >> 2)) * 8);
        if (tid == 0) TSTAMP(18);
        const uint32_t wos = sm + OFF_RING + ((19 + (warp >> 2)) % NSLOT) * CHUNK;
        #pragma unroll
        for (int s = 0; s < 4; s++) {
            const int row = (warp & 3) * 64 + s * 16 + (mj >> 1) * 8 + mr;
            const uint32_t b0 = hadd2_bf16(ov[s].x, ov[4 + s].x), b1 = hadd2_bf16(ov[s].y, ov[4 + s].y);
            #pragma unroll
            for (int j = 0; j < 2; j++) {
                uint32_t a[4];
                ldsm4t(a, wos + row * 64 + (((2 * j + (mj & 1)) ^ ((row >> 1) & 3)) << 4));
                mma16816(ac[j], a, b0, b1);
            }
        }
        if (warp < 7) {
            mbar_wait(bar_full + 21 * 8);
            const uint32_t w2s = sm + OFF_RING + (21 % NSLOT) * CHUNK;
            #pragma unroll
            for (int s = 0; s < 2; s++) {
                const int row = warp * 32 + s * 16 + (mj >> 1) * 8 + mr;
                #pragma unroll
                for (int j = 0; j < 2; j++) {
                    uint32_t a[4];
                    ldsm4t(a, w2s + row * 64 + (((2 * j + (mj & 1)) ^ ((row >> 1) & 3)) << 4));
                    mma16816(af[j], a, hb[s][0], hb[s][1]);
                }
            }
        }
        float* r0 = red + (warp * 8 + 2 * t) * RED_PITCH + gl;
        #pragma unroll
        for (int j = 0; j < 2; j++) {
            r0[j * 16] = ac[j][0] + af[j][0]; r0[RED_PITCH + j * 16] = ac[j][1] + af[j][1];
            r0[j * 16 + 8] = ac[j][2] + af[j][2]; r0[RED_PITCH + j * 16 + 8] = ac[j][3] + af[j][3];
        }
    }
    cbar();
    if (tid == 0) TSTAMP(19);
    float part = 0.f;
    #pragma unroll
    for (int w = 0; w < 8; w++) part += red[(w * 8 + warp) * RED_PITCH + lane];
    if (warp != g) {
        st_rlx(g_part + cta * 256 + warp * 32 + lane, nz(__float_as_uint(part)));
    } else {
        uint32_t pv[8];
        const uint32_t* pp = g_part + c * 256 + g * 32 + lane;
        #pragma unroll
        for (int k = 0; k < 8; k++) pv[k] = (k == g) ? nz(__float_as_uint(part)) : ld_rlx(pp + k * 4096);
        for (uint32_t it = 0; ; ++it) {
            bool ok = true;
            #pragma unroll
            for (int k = 0; k < 8; k++) {
                if (pv[k] == 0u) { pv[k] = ld_rlx(pp + k * 4096); ok = false; }
            }
            if (ok) break;
            if (it > SPIN_LIMIT) __trap();
        }
        float s = resid;
        #pragma unroll
        for (int k = 0; k < 8; k++) s += __uint_as_float(pv[k]);
        out[g * 512 + c * 32 + lane] = __float2bfloat16_rn(s);
        __syncwarp();
        if (cta == 0 && lane == 0) st_rlx(&g_epoch, tag);
        if (lane == 0) TSTAMP(20);
    }
}

typedef CUresult (*EncodeFn)(CUtensorMap*, CUtensorMapDataType, cuuint32_t, void*, const cuuint64_t*, const cuuint64_t*,
                             const cuuint32_t*, const cuuint32_t*, CUtensorMapInterleave, CUtensorMapSwizzle,
                             CUtensorMapL2promotion, CUtensorMapFloatOOBfill);

void encode(EncodeFn fn, CUtensorMap* m, const void* p, int rank, const cuuint64_t* dims, const cuuint64_t* strides,
            const cuuint32_t* box, CUtensorMapSwizzle sw) {
    const cuuint32_t es[3] = {1, 1, 1};
    fn(m, CU_TENSOR_MAP_DATA_TYPE_BFLOAT16, rank, const_cast<void*>(p), dims, strides, box, es,
       CU_TENSOR_MAP_INTERLEAVE_NONE, sw, CU_TENSOR_MAP_L2_PROMOTION_L2_256B, CU_TENSOR_MAP_FLOAT_OOB_FILL_NONE);
}

}

extern "C" void kernel_launch(void* const* d_in, const int* in_sizes, int n_in, void* d_out, int out_size) {
    (void)in_sizes; (void)n_in; (void)out_size;
    static EncodeFn fn = nullptr;
    if (!fn) {
        cudaDriverEntryPointQueryResult qr;
        cudaGetDriverEntryPoint("cuTensorMapEncodeTiled", (void**)&fn, cudaEnableDefault, &qr);
        cudaFuncSetAttribute(fused_decode_kernel, cudaFuncAttributeMaxDynamicSharedMemorySize, SMEM_BYTES);
    }
    Maps m;
    {
        const cuuint64_t d[3] = {64, 64ull * 4096, 2}, s[2] = {256, 128};
        const cuuint32_t bx[3] = {64, 64, 2};
        encode(fn, &m.k, d_in[1], 3, d, s, bx, CU_TENSOR_MAP_SWIZZLE_128B);
        encode(fn, &m.v, d_in[2], 3, d, s, bx, CU_TENSOR_MAP_SWIZZLE_128B);
    }
    { const cuuint64_t d[2] = {4096, 512}, s[1] = {8192}; const cuuint32_t bx[2] = {32, 256};
      encode(fn, &m.wq, d_in[3], 2, d, s, bx, CU_TENSOR_MAP_SWIZZLE_64B); }
    { const cuuint64_t d[2] = {512, 4096}, s[1] = {1024}; const cuuint32_t bx[2] = {32, 256};
      encode(fn, &m.wo, d_in[4], 2, d, s, bx, CU_TENSOR_MAP_SWIZZLE_64B); }
    { const cuuint64_t d[2] = {1792, 512}, s[1] = {3584}; const cuuint32_t bx[2] = {16, 256};
      encode(fn, &m.w1, d_in[6], 2, d, s, bx, CU_TENSOR_MAP_SWIZZLE_32B); }
    { const cuuint64_t d[2] = {512, 1792}, s[1] = {1024}; const cuuint32_t bx[2] = {32, 224};
      encode(fn, &m.w2, d_in[7], 2, d, s, bx, CU_TENSOR_MAP_SWIZZLE_64B); }
    fused_decode_kernel<<<NCTA, NTHREADS, SMEM_BYTES, cudaStreamPerThread>>>(
        m, (const __nv_bfloat16*)d_in[0], (const char*)d_in[3], (__nv_bfloat16*)d_out);
}
```

```cpp
#include <cuda_runtime.h>
#include <cuda_bf16.h>
#include <cuda.h>
#include <stdint.h>

namespace {

constexpr int NCTA = 128;
constexpr int CLUSTER = 16;
#define GHOST 0
constexpr int NTHREADS = 288 + 32 * GHOST;
constexpr int CHUNK = 16384;
constexpr int NSLOT = 6;
constexpr int NCHUNK = 22;
constexpr int C_K = 3, C_V = 11, C_W2 = 19, C_WO = 20;
#define YIELD 1
#define DEPTH 4
#define PF_BYTES 8192
#define WARM 1
#define R_DELAY 0
constexpr uint32_t SPIN_LIMIT = 1u << 24;

constexpr int RED_PITCH = 52;
constexpr int OFF_RING = 0;
constexpr int OFF_U = NSLOT * CHUNK;
constexpr int OFF_X = OFF_U;
constexpr int OFF_RED = OFF_U;
constexpr int OFF_P = OFF_U;
constexpr int OFF_O = OFF_U + 4096;
constexpr int OFF_OST = OFF_O + 4352;
constexpr int OFF_DRED = OFF_OST + 1024;
constexpr int OFF_Q = OFF_U + 13312;
constexpr int OFF_H = OFF_Q + 1024;
constexpr int OFF_ML = OFF_H + 1152;
constexpr int OFF_STAT = OFF_ML + 32;
constexpr int OFF_BAR = OFF_STAT + 592;
constexpr int NBAR = 43;
constexpr int OFF_TS = OFF_BAR + NBAR * 8 + 8;
constexpr int SMEM_BYTES = OFF_TS + 64 * 4 + 16;
static_assert(2 * (SMEM_BYTES + 1024) <= 233472, "two CTAs per SM");

struct Maps { CUtensorMap x, wq, k, v, w1, wo, w2; };

__device__ unsigned int g_epoch;
__device__ __align__(128) uint32_t g_part[NCTA * 1024];

#define TSTAMP(idx) do { } while (0)

__device__ __forceinline__ uint32_t smem_u32(const void* p) { return (uint32_t)__cvta_generic_to_shared(p); }
__device__ __forceinline__ void mbar_init(uint32_t bar, uint32_t cnt) {
    asm volatile("mbarrier.init.shared::cta.b64 [%0], %1;" :: "r"(bar), "r"(cnt) : "memory");
}
__device__ __forceinline__ void mbar_expect(uint32_t bar, uint32_t bytes) {
    asm volatile("mbarrier.arrive.expect_tx.shared::cta.b64 _, [%0], %1;" :: "r"(bar), "r"(bytes) : "memory");
}
__device__ __forceinline__ void mbar_arrive(uint32_t bar) {
    asm volatile("mbarrier.arrive.shared::cta.b64 _, [%0];" :: "r"(bar) : "memory");
}
__device__ __forceinline__ void mbar_wait(uint32_t bar) {
    uint32_t done;
    for (uint32_t it = 0; ; ++it) {
        asm volatile("{\n.reg .pred p;\nmbarrier.try_wait.parity.shared::cta.b64 p, [%1], 0;\nselp.u32 %0, 1, 0, p;\n}"
                     : "=r"(done) : "r"(bar) : "memory");
        if (done) break;
        if (it > SPIN_LIMIT) __trap();
    }
}
__device__ __forceinline__ uint32_t mapa(uint32_t addr, uint32_t rank) {
    uint32_t r; asm("mapa.shared::cluster.u32 %0, %1, %2;" : "=r"(r) : "r"(addr), "r"(rank)); return r;
}
__device__ __forceinline__ void st_async2(uint32_t dst, uint32_t a, uint32_t b, uint32_t bar) {
    asm volatile("st.async.weak.shared::cluster.mbarrier::complete_tx::bytes.v2.b32 [%0], {%1,%2}, [%3];"
                 :: "r"(dst), "r"(a), "r"(b), "r"(bar) : "memory");
}
__device__ __forceinline__ void st_async4(uint32_t dst, uint32_t a, uint32_t b, uint32_t c, uint32_t d, uint32_t bar) {
    asm volatile("st.async.weak.shared::cluster.mbarrier::complete_tx::bytes.v4.b32 [%0], {%1,%2,%3,%4}, [%5];"
                 :: "r"(dst), "r"(a), "r"(b), "r"(c), "r"(d), "r"(bar) : "memory");
}
__device__ __forceinline__ void tma2d(uint32_t dst, const CUtensorMap* m, int c0, int c1, uint32_t bar) {
    asm volatile("cp.async.bulk.tensor.2d.shared::cluster.global.mbarrier::complete_tx::bytes [%0], [%1, {%3, %4}], [%2];"
                 :: "r"(dst), "l"(m), "r"(bar), "r"(c0), "r"(c1) : "memory");
}
__device__ __forceinline__ void tma3d(uint32_t dst, const CUtensorMap* m, int c0, int c1, int c2, uint32_t bar) {
    asm volatile("cp.async.bulk.tensor.3d.shared::cluster.global.mbarrier::complete_tx::bytes [%0], [%1, {%3, %4, %5}], [%2];"
                 :: "r"(dst), "l"(m), "r"(bar), "r"(c0), "r"(c1), "r"(c2) : "memory");
}
__device__ __forceinline__ void bulk_g2s(uint32_t dst, const void* src, uint32_t bytes, uint32_t bar) {
    asm volatile("cp.async.bulk.shared::cluster.global.mbarrier::complete_tx::bytes [%0], [%1], %2, [%3];"
                 :: "r"(dst), "l"(src), "r"(bytes), "r"(bar) : "memory");
}
__device__ __forceinline__ void l2_prefetch(const void* src, uint32_t bytes) {
    asm volatile("cp.async.bulk.prefetch.L2.global [%0], %1;" :: "l"(src), "r"(bytes) : "memory");
}
__device__ __forceinline__ void ldsm4(uint32_t (&r)[4], uint32_t addr) {
    asm volatile("ldmatrix.sync.aligned.m8n8.x4.shared.b16 {%0,%1,%2,%3}, [%4];"
                 : "=r"(r[0]), "=r"(r[1]), "=r"(r[2]), "=r"(r[3]) : "r"(addr) : "memory");
}
__device__ __forceinline__ void ldsm4t(uint32_t (&r)[4], uint32_t addr) {
    asm volatile("ldmatrix.sync.aligned.m8n8.x4.trans.shared.b16 {%0,%1,%2,%3}, [%4];"
                 : "=r"(r[0]), "=r"(r[1]), "=r"(r[2]), "=r"(r[3]) : "r"(addr) : "memory");
}
__device__ __forceinline__ void ldsm2t(uint32_t& r0, uint32_t& r1, uint32_t addr) {
    asm volatile("ldmatrix.sync.aligned.m8n8.x2.trans.shared.b16 {%0,%1}, [%2];" : "=r"(r0), "=r"(r1) : "r"(addr) : "memory");
}
__device__ __forceinline__ void mma16816(float (&d)[4], const uint32_t (&a)[4], uint32_t b0, uint32_t b1) {
    asm volatile("mma.sync.aligned.m16n8k16.row.col.f32.bf16.bf16.f32 {%0,%1,%2,%3}, {%4,%5,%6,%7}, {%8,%9}, {%0,%1,%2,%3};"
                 : "+f"(d[0]), "+f"(d[1]), "+f"(d[2]), "+f"(d[3])
                 : "r"(a[0]), "r"(a[1]), "r"(a[2]), "r"(a[3]), "r"(b0), "r"(b1));
}
__device__ __forceinline__ void mma1688(float (&d)[4], uint32_t a0, uint32_t a1, uint32_t b0) {
    asm volatile("mma.sync.aligned.m16n8k8.row.col.f32.bf16.bf16.f32 {%0,%1,%2,%3}, {%4,%5}, {%6}, {%0,%1,%2,%3};"
                 : "+f"(d[0]), "+f"(d[1]), "+f"(d[2]), "+f"(d[3]) : "r"(a0), "r"(a1), "r"(b0));
}
__device__ __forceinline__ uint32_t movtrans(uint32_t a) {
    uint32_t d;
    asm volatile("movmatrix.sync.aligned.m8n8.trans.b16 %0, %1;" : "=r"(d) : "r"(a));
    return d;
}
__device__ __forceinline__ uint32_t pack_bf16(float lo, float hi) {
    uint32_t d;
    asm("cvt.rn.bf16x2.f32 %0, %1, %2;" : "=r"(d) : "f"(hi), "f"(lo));
    return d;
}
__device__ __forceinline__ float bf16r(float x) { return __bfloat162float(__float2bfloat16_rn(x)); }
__device__ __forceinline__ float bf_lo(uint32_t u) { return __uint_as_float(u << 16); }
__device__ __forceinline__ float bf_hi(uint32_t u) { return __uint_as_float(u & 0xffff0000u); }
__device__ __forceinline__ uint32_t hadd2_bf16(uint32_t a, uint32_t b) {
    uint32_t d;
    asm("add.rn.bf16x2 %0, %1, %2;" : "=r"(d) : "r"(a), "r"(b));
    return d;
}
__device__ __forceinline__ uint32_t ld_rlx(const uint32_t* p) {
    uint32_t v; asm volatile("ld.relaxed.gpu.global.u32 %0, [%1];" : "=r"(v) : "l"(p) : "memory"); return v;
}
__device__ __forceinline__ uint4 ld_rlx4(const uint32_t* p) {
    uint4 v;
    asm volatile("ld.relaxed.gpu.global.v4.u32 {%0,%1,%2,%3}, [%4];" : "=r"(v.x), "=r"(v.y), "=r"(v.z), "=r"(v.w) : "l"(p) : "memory");
    return v;
}
__device__ __forceinline__ void st_rlx(uint32_t* p, uint32_t v) {
    asm volatile("st.relaxed.gpu.global.u32 [%0], %1;" :: "l"(p), "r"(v) : "memory");
}
__device__ __forceinline__ void st_rlx4(uint32_t* p, uint32_t a, uint32_t b, uint32_t c, uint32_t d) {
    asm volatile("st.relaxed.gpu.global.v4.u32 [%0], {%1,%2,%3,%4};" :: "l"(p), "r"(a), "r"(b), "r"(c), "r"(d) : "memory");
}
__device__ __forceinline__ uint32_t tagw(float v, uint32_t tag) { return (__float_as_uint(v) & ~1u) | tag; }
__device__ __forceinline__ bool tagged(const uint4& v, uint32_t tag) {
    return (((v.x ^ tag) | (v.y ^ tag) | (v.z ^ tag) | (v.w ^ tag)) & 1u) == 0u;
}
__device__ __forceinline__ void spin_cycles(int n) { const long long t0 = clock64(); while (clock64() - t0 < n) { } }
__device__ __forceinline__ void cbar() { asm volatile("bar.sync 1, 256;" ::: "memory"); }
__device__ __forceinline__ float ex2(float x) { float y; asm("ex2.approx.ftz.f32 %0, %1;" : "=f"(y) : "f"(x)); return y; }

__global__ void __launch_bounds__(NTHREADS, 2)
fused_decode_kernel(const __grid_constant__ Maps maps, const char* __restrict__ wq_raw, __nv_bfloat16* __restrict__ out)
{
    extern __shared__ __align__(1024) char smp[];
    const uint32_t sm = smem_u32(smp);
    int tid = threadIdx.x, warp = tid >> 5;
    const int lane = tid & 31;
    const int cta = blockIdx.x, g = cta >> 4, c = cta & 15, b = c >> 1, half = c & 1;
    const int hh = cta >> 2, cq = cta & 3;
    const bool ffn = g < 7;
    const uint32_t bar_full = sm + OFF_BAR, bar_empty = bar_full + NCHUNK * 8;
    const uint32_t bar_q = bar_empty + 16 * 8, bar_h = bar_q + 8, bar_ml = bar_q + 16, bar_o = bar_q + 24, bar_x = bar_q + 32;
    const int rj = cta >> 2, ru = lane & 7, rp = lane >> 3;

    if (__builtin_expect(warp == 8, 1)) {
        if (lane == 0 && PF_BYTES) l2_prefetch(wq_raw + (size_t)cta * 32768, PF_BYTES);
        if (lane == 0) {
            mbar_init(bar_x, 1); mbar_init(bar_full, 1); mbar_init(bar_full + 8, 1);
            asm volatile("fence.proxy.async.shared::cta;" ::: "memory");
            TSTAMP(57);
            mbar_expect(bar_x, 8192); tma3d(sm + OFF_X, &maps.x, 0, 0, 0, bar_x);
            mbar_expect(bar_full, CHUNK); tma2d(sm, &maps.wq, cta * 32, 0, bar_full);
            mbar_expect(bar_full + 8, CHUNK); tma2d(sm + CHUNK, &maps.wq, cta * 32, 256, bar_full + 8);
            TSTAMP(58);
            if (sm & 1023u) __trap();
            #pragma unroll
            for (int s = 2; s < NCHUNK; s++) mbar_init(bar_full + s * 8, 1);
            #pragma unroll
            for (int s = 0; s < 16; s++) mbar_init(bar_empty + s * 8, s < 2 ? 4 : (s >= C_K && s < C_V) ? 1 : 8);
            #pragma unroll
            for (int s = 0; s < 4; s++) mbar_init(bar_q + s * 8, 1);
            mbar_expect(bar_q, 1024); mbar_expect(bar_h, 1024); mbar_expect(bar_ml, 32); mbar_expect(bar_o, 4096);
            asm volatile("fence.mbarrier_init.release.cluster;" ::: "memory");
            asm volatile("fence.proxy.async.shared::cta;" ::: "memory");
        }
        if (lane == 0) TSTAMP(59);
        __syncwarp();
        asm volatile("barrier.cluster.arrive.relaxed.aligned;" ::: "memory");
        asm volatile("bar.arrive 2, %0;" :: "n"(NTHREADS) : "memory");
        if (lane == 0) {
            TSTAMP(33);
            if (ffn) {
                mbar_expect(bar_full + 16, CHUNK);
                tma2d(sm + 2 * CHUNK, &maps.w1, cta * 16, 0, bar_full + 16);
                tma2d(sm + 2 * CHUNK + 8192, &maps.w1, cta * 16, 256, bar_full + 16);
            } else mbar_arrive(bar_full + 16);
            const int row0 = (b * 8 + g) * 4096 + 3072 + half * 512;
            uint32_t dst = sm + C_K * CHUNK;
            #pragma unroll 1
            for (int ch = C_K; ch < NCHUNK; ch++) {
                if (ch >= DEPTH) mbar_wait(bar_full + (ch < C_W2 ? ch - DEPTH : min(ch - DEPTH + YIELD, C_W2 - 1)) * 8);
                if (ch >= NSLOT) mbar_wait(bar_empty + (ch - NSLOT) * 8);
                const uint32_t bar = bar_full + ch * 8;
                if (ch == C_W2 && !ffn) mbar_arrive(bar);
                else {
                    mbar_expect(bar, CHUNK);
                    const CUtensorMap* m = ch < C_V ? &maps.k : ch < C_W2 ? &maps.v : ch == C_W2 ? &maps.w2 : &maps.wo;
                    const int row = ch < C_W2 ? row0 + ((ch - C_K) & 7) * 64 : ch == C_W2 ? hh * 64 : hh * 128 + (ch - C_WO) * 64;
                    tma3d(dst, m, 0, row, ch < C_W2 ? 0 : cq * 2, bar);
                }
                dst = (dst == sm + (NSLOT - 1) * CHUNK) ? sm : dst + CHUNK;
                TSTAMP(32 + ch);
            }
        }
        __syncwarp();
        {
            uint32_t acc = 0;
            const uint32_t* pp = g_part + (rp * 4 + cq) * 1024 + rj * 32 + ru * 4;
            uint4 v[8];
            #pragma unroll
            for (int i = 0; i < 8; i++) v[i] = ld_rlx4(pp + i * 16384);
            #pragma unroll
            for (int i = 0; i < 8; i++) acc |= v[i].x;
            if (acc == 0x7fc12345u) *reinterpret_cast<volatile uint32_t*>(smp + OFF_STAT + 584) = acc;
        }
        asm volatile("barrier.cluster.wait.aligned;" ::: "memory");
        return;
    }

    if (tid == 0) TSTAMP(55);
    const bool real = warp < 8;
    warp &= 7;
    tid = warp * 32 + lane;
    asm volatile("barrier.cluster.arrive.relaxed.aligned;" ::: "memory");
    const int gl = lane >> 2, t = lane & 3;
    float* lnst = reinterpret_cast<float*>(smp + OFF_STAT + 512);
    volatile uint32_t* epoch_s = reinterpret_cast<volatile uint32_t*>(smp + OFF_STAT + 580);
    const int oidx = (2 * (ru & 3) + (rp & 1)) * 512 + cq * 128 + (rj >> 2) * 16 + 2 * (rj & 3) + (ru >> 2) + 8 * (rp >> 1);
    if (tid == 0 && real) *epoch_s = ld_rlx(&g_epoch);
    asm volatile("bar.sync 2, %0;" :: "n"(NTHREADS) : "memory");
    if (real) mbar_wait(bar_x);
    if (tid == 0 && real) TSTAMP(5);
    uint32_t xf[8];
    #pragma unroll
    for (int j = 0; j < 8; j++)
        xf[j] = *reinterpret_cast<const uint32_t*>(smp + OFF_X + warp * 1024 + gl * 128 + ((j ^ gl) << 4) + t * 4);
    float resid;
    {
        const int ob = oidx >> 9, ocol = oidx & 511;
        resid = __bfloat162float(*reinterpret_cast<const __nv_bfloat16*>(
            smp + OFF_X + (ocol >> 6) * 1024 + ob * 128 + ((((ocol >> 3) & 7) ^ ob) << 4) + (ocol & 7) * 2));
    }
    {
        const char* xr = smp + OFF_X + (lane >> 3) * 1024 + warp * 128 + (lane & 7) * 16;
        const uint4 xa = *reinterpret_cast<const uint4*>(xr), xb = *reinterpret_cast<const uint4*>(xr + 4096);
        const float sh = bf_lo(*reinterpret_cast<const uint32_t*>(smp + OFF_X + warp * 128));
        const uint32_t w[8] = {xa.x, xa.y, xa.z, xa.w, xb.x, xb.y, xb.z, xb.w};
        float s4[4] = {}, q4[4] = {};
        #pragma unroll
        for (int j = 0; j < 8; j++) {
            const float lo = bf_lo(w[j]) - sh, hi = bf_hi(w[j]) - sh;
            s4[j & 3] += lo + hi;
            q4[j & 3] = fmaf(lo, lo, fmaf(hi, hi, q4[j & 3]));
        }
        float s = (s4[0] + s4[1]) + (s4[2] + s4[3]), q2 = (q4[0] + q4[1]) + (q4[2] + q4[3]);
        #pragma unroll
        for (int o = 16; o > 0; o >>= 1) {
            s += __shfl_xor_sync(0xffffffffu, s, o);
            q2 += __shfl_xor_sync(0xffffffffu, q2, o);
        }
        const float ms = s * (1.f / 512.f), mean = sh + ms;
        q2 = fmaxf(fmaf(-ms, s, q2), 0.f);
        const float den = bf16r(__fsqrt_rn(bf16r(bf16r(q2 * (1.f / 512.f)) + 1e-5f)));
        if (lane == 0 && real) *reinterpret_cast<float2*>(lnst + warp * 2) = make_float2(bf16r(mean), __frcp_rn(den));
    }
    if (real) cbar();
    if (tid == 0 && real) TSTAMP(6);
    {
        const float2 st = *reinterpret_cast<const float2*>(lnst + gl * 2);
        #pragma unroll
        for (int j = 0; j < 8; j++)
            xf[j] = pack_bf16(bf16r(bf_lo(xf[j]) - st.x) * st.y, bf16r(bf_hi(xf[j]) - st.x) * st.y);
    }
    const uint32_t tag = (*epoch_s + 1u) & 1u;
    if (tid == 0 && real) TSTAMP(1);

    float* red = reinterpret_cast<float*>(smp + OFF_RED);
    const int mj = lane >> 3, mr = lane & 7;
    float* r0 = red + (warp * 8 + 2 * t) * RED_PITCH + gl;
    {
        float aq[2][4] = {};
        if (real) mbar_wait(bar_full + (warp >> 2) * 8);
        const uint32_t wqs = sm + OFF_RING + (warp >> 2) * CHUNK;
        #pragma unroll
        for (int s = 0; s < 4; s++) {
            const int row = (warp & 3) * 64 + s * 16 + (mj >> 1) * 8 + mr;
            #pragma unroll
            for (int j = 0; j < 2; j++) {
                uint32_t a[4];
                ldsm4t(a, wqs + row * 64 + (((2 * j + (mj & 1)) ^ ((row >> 1) & 3)) << 4));
                mma16816(aq[j], a, xf[2 * s], xf[2 * s + 1]);
            }
        }
        __syncwarp();
        if (lane == 0 && real) mbar_arrive(bar_empty + (warp >> 2) * 8);
        if (real) {
            #pragma unroll
            for (int j = 0; j < 2; j++) {
                r0[j * 16] = aq[j][0]; r0[RED_PITCH + j * 16] = aq[j][1];
                r0[j * 16 + 8] = aq[j][2]; r0[RED_PITCH + j * 16 + 8] = aq[j][3];
            }
        }
    }
    if (real) cbar();
    if (real) asm volatile("barrier.cluster.wait.aligned;" ::: "memory");
    if (warp < 4) {
        const int bb = tid >> 4, wd = tid & 15;
        const int col = (wd >> 3) * 16 + ((wd >> 1) & 3) * 2 + (wd & 1) * 8;
        float s0 = 0.f, s1 = 0.f;
        #pragma unroll
        for (int w = 0; w < 8; w++) {
            const float2 f = *reinterpret_cast<const float2*>(red + (w * 8 + bb) * RED_PITCH + col);
            s0 += f.x; s1 += f.y;
        }
        const uint32_t u = pack_bf16(s0, s1);
        const int q0 = (lane & 16) + (lane & 3) * 4;
        const uint32_t u0 = __shfl_sync(0xffffffffu, u, q0), u1 = __shfl_sync(0xffffffffu, u, q0 + 1);
        const uint32_t u2 = __shfl_sync(0xffffffffu, u, q0 + 2), u3 = __shfl_sync(0xffffffffu, u, q0 + 3);
        if (wd < 8 && real) {
            const uint32_t rank = 2 * bb + (wd >> 2);
            st_async4(mapa(sm + OFF_Q + c * 64 + (wd & 3) * 16, rank), u0, u1, u2, u3, mapa(bar_q, rank));
        }
    }
    if (tid == 0 && real) TSTAMP(2);
    if (ffn) {
        float ah[4] = {};
        if (real) mbar_wait(bar_full + 2 * 8);
        const uint32_t w1s = sm + OFF_RING + 2 * CHUNK;
        #pragma unroll
        for (int s = 0; s < 4; s++) {
            const int row = warp * 64 + s * 16 + (mj >> 1) * 8 + mr;
            uint32_t a[4];
            ldsm4t(a, w1s + row * 32 + (((mj & 1) ^ ((row >> 2) & 1)) << 4));
            mma16816(ah, a, xf[2 * s], xf[2 * s + 1]);
        }
        if (real) { r0[32] = ah[0]; r0[RED_PITCH + 32] = ah[1]; r0[40] = ah[2]; r0[RED_PITCH + 40] = ah[3]; }
    }
    __syncwarp();
    if (lane == 0 && real) mbar_arrive(bar_empty + 2 * 8);
    if (ffn) {
        if (real) cbar();
        if (warp >= 6 || !real) {
            const int bb = (tid & 63) >> 3, wd = tid & 7;
            float s0 = 0.f, s1 = 0.f;
            #pragma unroll
            for (int w = 0; w < 8; w++) {
                const float2 f = *reinterpret_cast<const float2*>(red + (w * 8 + bb) * RED_PITCH + 32 + 2 * wd);
                s0 += f.x; s1 += f.y;
            }
            s0 = bf16r(s0); s1 = bf16r(s1);
            s0 = __fdividef(s0, 1.f + __expf(-s0)); s1 = __fdividef(s1, 1.f + __expf(-s1));
            const uint32_t u = pack_bf16(s0, s1);
            const int q0 = (lane & 24) + (lane & 1) * 4;
            const uint32_t u0 = __shfl_sync(0xffffffffu, u, q0), u1 = __shfl_sync(0xffffffffu, u, q0 + 1);
            const uint32_t u2 = __shfl_sync(0xffffffffu, u, q0 + 2), u3 = __shfl_sync(0xffffffffu, u, q0 + 3);
            const uint32_t rank = (c & 12) + (wd >> 1);
            if (real) st_async4(mapa(sm + OFF_H + bb * 144 + ((c & 3) * 2 + (wd & 1)) * 16, rank), u0, u1, u2, u3, mapa(bar_h, rank));
        }
    }
    if (tid == 0 && real) TSTAMP(22);
    const int ach = 2 * warp + (mj & 1);
    const uint32_t voff = (ach >> 3) * 8192 + ((mj >> 1) * 8 + mr) * 128 + (((ach & 7) ^ mr) << 4);

    float sc[4][4];
    {
        if (real) mbar_wait(bar_q);
        if (tid == 0 && real) TSTAMP(3);
        uint32_t qb[8][2];
        #pragma unroll
        for (int s = 0; s < 8; s++) {
            const uint2 v = *reinterpret_cast<const uint2*>(smp + OFF_Q + (((gl & 3) * 8 + s) * 4 + t) * 8);
            qb[s][0] = v.x; qb[s][1] = v.y;
        }
        if (real) mbar_wait(bar_full + (C_K + warp) * 8);
        const uint32_t ks = sm + OFF_RING + ((C_K + warp) % NSLOT) * CHUNK;
        #pragma unroll
        for (int i = 0; i < 4; i++) { sc[i][0] = sc[i][1] = sc[i][2] = sc[i][3] = 0.f; }
        #pragma unroll
        for (int s = 0; s < 8; s++) {
            const int ch = 2 * s + (mj >> 1);
            #pragma unroll
            for (int i = 0; i < 4; i++) {
                const int row = i * 16 + (mj & 1) * 8 + mr;
                uint32_t a[4];
                ldsm4(a, ks + (ch >> 3) * 8192 + row * 128 + (((ch & 7) ^ mr) << 4));
                mma16816(sc[i], a, qb[s][0], qb[s][1]);
            }
        }
        __syncwarp();
        if (lane == 0 && real) mbar_arrive(bar_empty + (C_K + warp) * 8);
    }
    float* wmax = reinterpret_cast<float*>(smp + OFF_STAT);
    float* wsum = wmax + 64;
    float m0, m1;
    constexpr float L2E = 1.4426950408889634f;
    {
        m0 = -INFINITY; m1 = -INFINITY;
        #pragma unroll
        for (int i = 0; i < 4; i++) {
            #pragma unroll
            for (int k = 0; k < 4; k++) sc[i][k] = bf16r(bf16r(sc[i][k]) * 0.08838834764831845f);
            m0 = fmaxf(m0, fmaxf(sc[i][0], sc[i][2]));
            m1 = fmaxf(m1, fmaxf(sc[i][1], sc[i][3]));
        }
        #pragma unroll
        for (int o = 4; o < 32; o <<= 1) {
            m0 = fmaxf(m0, __shfl_xor_sync(0xffffffffu, m0, o));
            m1 = fmaxf(m1, __shfl_xor_sync(0xffffffffu, m1, o));
        }
        if (lane < 4 && real) *reinterpret_cast<float2*>(wmax + warp * 8 + 2 * lane) = make_float2(m0, m1);
        if (real) cbar();
        #pragma unroll
        for (int w = 0; w < 8; w++) {
            const float2 f = *reinterpret_cast<const float2*>(wmax + w * 8 + 2 * t);
            m0 = fmaxf(m0, f.x); m1 = fmaxf(m1, f.y);
        }
        float l0 = 0.f, l1 = 0.f;
        uint32_t pw[4][2];
        #pragma unroll
        for (int i = 0; i < 4; i++) {
            const float p0 = ex2((sc[i][0] - m0) * L2E), p1 = ex2((sc[i][1] - m1) * L2E);
            const float p2 = ex2((sc[i][2] - m0) * L2E), p3 = ex2((sc[i][3] - m1) * L2E);
            l0 += p0 + p2; l1 += p1 + p3;
            pw[i][0] = movtrans(pack_bf16(p0, p1));
            pw[i][1] = movtrans(pack_bf16(p2, p3));
        }
        if (lane < 16 && real) {
            uint4* pd = reinterpret_cast<uint4*>(smp + OFF_P) + (warp * 2) * 16 + lane;
            pd[0] = make_uint4(pw[0][0], pw[0][1], pw[1][0], pw[1][1]);
            pd[16] = make_uint4(pw[2][0], pw[2][1], pw[3][0], pw[3][1]);
        }
        #pragma unroll
        for (int o = 4; o < 32; o <<= 1) {
            l0 += __shfl_xor_sync(0xffffffffu, l0, o);
            l1 += __shfl_xor_sync(0xffffffffu, l1, o);
        }
        if (lane < 4 && real) *reinterpret_cast<float2*>(wsum + warp * 8 + 2 * lane) = make_float2(l0, l1);
    }
    if (real) cbar();
    float l0 = 0.f, l1 = 0.f;
    #pragma unroll
    for (int w = 0; w < 8; w++) {
        const float2 f = *reinterpret_cast<const float2*>(wsum + w * 8 + 2 * t);
        l0 += f.x; l1 += f.y;
    }
    if (tid < 2 && real) {
        const uint32_t dst = mapa(sm + OFF_ML + tid * 8, c ^ 1), bar = mapa(bar_ml, c ^ 1);
        st_async2(dst, __float_as_uint(m0), __float_as_uint(m1), bar);
        st_async2(dst + 16, __float_as_uint(l0), __float_as_uint(l1), bar);
    }
    if (tid == 0 && real) TSTAMP(4);

    float f0 = 0.f, f1 = 0.f;
    float oc[4][4] = {};
    {
        const uint4* pfp = reinterpret_cast<const uint4*>(smp + OFF_P) + (lane & 15);
        uint32_t vs = sm + OFF_RING + (C_V % NSLOT) * CHUNK;
        #pragma unroll 1
        for (int j = 0; j < 8; j++) {
            const uint4 pa = pfp[j * 32], pb = pfp[j * 32 + 16];
            if (j == 6) {
                if (real) mbar_wait(bar_ml);
                const float* pm = reinterpret_cast<const float*>(smp + OFF_ML) + (t & 1) * 2;
                const float mo0 = pm[0], mo1 = pm[1];
                const float mt0 = fmaxf(m0, mo0), mt1 = fmaxf(m1, mo1);
                const float e0 = ex2((m0 - mt0) * L2E), e1 = ex2((m1 - mt1) * L2E);
                f0 = __fdividef(e0, l0 * e0 + pm[4] * ex2((mo0 - mt0) * L2E));
                f1 = __fdividef(e1, l1 * e1 + pm[5] * ex2((mo1 - mt1) * L2E));
            }
            if (real) mbar_wait(bar_full + (C_V + j) * 8);
            if (tid == 0 && real) TSTAMP(8 + j);
            uint32_t a[4][4];
            #pragma unroll
            for (int s = 0; s < 4; s++) ldsm4t(a[s], vs + voff + s * 2048);
            mma16816(oc[0], a[0], pa.x, pa.y);
            mma16816(oc[1], a[1], pa.z, pa.w);
            mma16816(oc[2], a[2], pb.x, pb.y);
            mma16816(oc[3], a[3], pb.z, pb.w);
            __syncwarp();
            if (j < 5 && lane == 0 && real) mbar_arrive(bar_empty + (C_V + j) * 8);
            vs = (vs == sm + (NSLOT - 1) * CHUNK) ? sm : vs + CHUNK;
        }
    }
    {
        const float o0 = (oc[0][0] + oc[1][0]) + (oc[2][0] + oc[3][0]);
        const float o1 = (oc[0][1] + oc[1][1]) + (oc[2][1] + oc[3][1]);
        const float o2 = (oc[0][2] + oc[1][2]) + (oc[2][2] + oc[3][2]);
        const float o3 = (oc[0][3] + oc[1][3]) + (oc[2][3] + oc[3][3]);
        const uint32_t u0 = movtrans(pack_bf16(o0 * f0, o1 * f1));
        const uint32_t u1 = movtrans(pack_bf16(o2 * f0, o3 * f1));
        if (lane < 16 && real)
            *reinterpret_cast<uint2*>(smp + OFF_OST + gl * 256 + (t * 4 + ((warp >> 1) ^ (t & 2))) * 16 + (warp & 1) * 8) = make_uint2(u0, u1);
        if (real) cbar();
        const uint32_t rank = tid >> 4;
        const uint4 v = *reinterpret_cast<const uint4*>(smp + OFF_OST + (rank >> 2) * 256 + (tid & 15) * 16);
        if (real) st_async4(mapa(sm + OFF_O + half * 2176 + b * 272 + (tid & 15) * 16, rank), v.x, v.y, v.z, v.w, mapa(bar_o, rank));
    }
    if (tid == 0 && real) TSTAMP(16);

    {
        float ac[4][4] = {};
        if (ffn) {
            if (real) { mbar_wait(bar_h); mbar_wait(bar_full + C_W2 * 8); }
            const uint32_t* hs = reinterpret_cast<const uint32_t*>(smp + OFF_H) + gl * 36 + t;
            #pragma unroll
            for (int s = 0; s < 4; s++) {
                uint32_t a[4];
                ldsm4t(a, sm + OFF_RING + (C_W2 % NSLOT) * CHUNK + voff + s * 2048);
                mma16816(ac[s], a, hs[s * 8], hs[s * 8 + 4]);
            }
        }
        if (tid == 0 && real) TSTAMP(23);
        if (real) mbar_wait(bar_o);
        if (tid == 0 && real) TSTAMP(17);
        uint32_t ob[8][2];
        const char* os = smp + OFF_O + gl * 272 + t * 64;
        #pragma unroll
        for (int s2 = 0; s2 < 4; s2++) {
            const uint4 o = *reinterpret_cast<const uint4*>(os + ((s2 ^ (t & 2)) << 4));
            const uint4 p = *reinterpret_cast<const uint4*>(os + 2176 + ((s2 ^ (t & 2)) << 4));
            ob[2 * s2][0] = hadd2_bf16(o.x, p.x); ob[2 * s2][1] = hadd2_bf16(o.y, p.y);
            ob[2 * s2 + 1][0] = hadd2_bf16(o.z, p.z); ob[2 * s2 + 1][1] = hadd2_bf16(o.w, p.w);
        }
        #pragma unroll
        for (int i = 0; i < 2; i++) {
            if (real) mbar_wait(bar_full + (C_WO + i) * 8);
            if (tid == 0 && real) TSTAMP(24 + i);
            #pragma unroll
            for (int s = 0; s < 4; s++) {
                uint32_t a[4];
                ldsm4t(a, sm + OFF_RING + ((C_WO + i) % NSLOT) * CHUNK + voff + s * 2048);
                mma16816(ac[s], a, ob[i * 4 + s][0], ob[i * 4 + s][1]);
            }
        }
        if (real) st_rlx4(g_part + cta * 1024 + tid * 4,
                          tagw((ac[0][0] + ac[1][0]) + (ac[2][0] + ac[3][0]), tag), tagw((ac[0][1] + ac[1][1]) + (ac[2][1] + ac[3][1]), tag),
                          tagw((ac[0][2] + ac[1][2]) + (ac[2][2] + ac[3][2]), tag), tagw((ac[0][3] + ac[1][3]) + (ac[2][3] + ac[3][3]), tag));
    }
    if (tid == 0 && real) TSTAMP(19);

    {
        if (R_DELAY) spin_cycles(R_DELAY);
        const uint32_t* pp = g_part + ((warp * 4 + rp) * 4 + cq) * 1024 + rj * 32 + ru * 4;
        uint4 v;
        for (uint32_t it = 0; ; ++it) {
            v = ld_rlx4(pp);
            if (__all_sync(0xffffffffu, tagged(v, tag)) || !real) break;
            if (it > SPIN_LIMIT) __trap();
        }
        const float s0 = __uint_as_float(v.x), s1 = __uint_as_float(v.y), s2 = __uint_as_float(v.z), s3 = __uint_as_float(v.w);
        float a = (rp & 1) ? s1 : s0, bq = (rp & 1) ? s3 : s2;
        a += __shfl_xor_sync(0xffffffffu, (rp & 1) ? s0 : s1, 8);
        bq += __shfl_xor_sync(0xffffffffu, (rp & 1) ? s2 : s3, 8);
        float r = (rp & 2) ? bq : a;
        r += __shfl_xor_sync(0xffffffffu, (rp & 2) ? a : bq, 16);
        float* dred = reinterpret_cast<float*>(smp + OFF_DRED);
        if (real) dred[warp * 32 + lane] = r;
        if (tid == 0 && real) TSTAMP(27);
        if (real) cbar();
        if (warp == 0 || !real) {
            float s = resid;
            #pragma unroll
            for (int w = 0; w < 8; w++) s += dred[w * 32 + lane];
            if (real) out[oidx] = __float2bfloat16_rn(s);
            if (cta == 0 && lane == 0 && real) st_rlx(&g_epoch, *epoch_s + 1u);
            if (lane == 0) TSTAMP(real ? 20 : 31);
        }
    }
}

typedef CUresult (*EncodeFn)(CUtensorMap*, CUtensorMapDataType, cuuint32_t, void*, const cuuint64_t*, const cuuint64_t*,
                             const cuuint32_t*, const cuuint32_t*, CUtensorMapInterleave, CUtensorMapSwizzle,
                             CUtensorMapL2promotion, CUtensorMapFloatOOBfill);

void encode(EncodeFn fn, CUtensorMap* m, const void* p, int rank, const cuuint64_t* dims, const cuuint64_t* strides,
            const cuuint32_t* box, CUtensorMapSwizzle sw) {
    const cuuint32_t es[3] = {1, 1, 1};
    fn(m, CU_TENSOR_MAP_DATA_TYPE_BFLOAT16, rank, const_cast<void*>(p), dims, strides, box, es,
       CU_TENSOR_MAP_INTERLEAVE_NONE, sw, CU_TENSOR_MAP_L2_PROMOTION_L2_256B, CU_TENSOR_MAP_FLOAT_OOB_FILL_NONE);
}

}

extern "C" void kernel_launch(void* const* d_in, const int* in_sizes, int n_in, void* d_out, int out_size) {
    (void)in_sizes; (void)n_in; (void)out_size;
    static EncodeFn fn = nullptr;
    if (!fn) {
        cudaDriverEntryPointQueryResult qr;
        cudaGetDriverEntryPoint("cuTensorMapEncodeTiled", (void**)&fn, cudaEnableDefault, &qr);
        cudaFuncSetAttribute(fused_decode_kernel, cudaFuncAttributeMaxDynamicSharedMemorySize, SMEM_BYTES);
        cudaFuncSetAttribute(fused_decode_kernel, cudaFuncAttributeNonPortableClusterSizeAllowed, 1);
    }
    Maps m;
    {
        const cuuint64_t d[3] = {64, 64ull * 4096, 2}, s[2] = {256, 128};
        const cuuint32_t bx[3] = {64, 64, 2};
        encode(fn, &m.k, d_in[1], 3, d, s, bx, CU_TENSOR_MAP_SWIZZLE_128B);
        encode(fn, &m.v, d_in[2], 3, d, s, bx, CU_TENSOR_MAP_SWIZZLE_128B);
    }
    { const cuuint64_t d[3] = {64, 8, 8}, s[2] = {1024, 128}; const cuuint32_t bx[3] = {64, 8, 8};
      encode(fn, &m.x, d_in[0], 3, d, s, bx, CU_TENSOR_MAP_SWIZZLE_128B); }
    { const cuuint64_t d[2] = {4096, 512}, s[1] = {8192}; const cuuint32_t bx[2] = {32, 256};
      encode(fn, &m.wq, d_in[3], 2, d, s, bx, CU_TENSOR_MAP_SWIZZLE_64B); }
    { const cuuint64_t d[3] = {64, 4096, 8}, s[2] = {1024, 128}; const cuuint32_t bx[3] = {64, 64, 2};
      encode(fn, &m.wo, d_in[4], 3, d, s, bx, CU_TENSOR_MAP_SWIZZLE_128B); }
    { const cuuint64_t d[2] = {1792, 512}, s[1] = {3584}; const cuuint32_t bx[2] = {16, 256};
      encode(fn, &m.w1, d_in[6], 2, d, s, bx, CU_TENSOR_MAP_SWIZZLE_32B); }
    { const cuuint64_t d[3] = {64, 1792, 8}, s[2] = {1024, 128}; const cuuint32_t bx[3] = {64, 64, 2};
      encode(fn, &m.w2, d_in[7], 3, d, s, bx, CU_TENSOR_MAP_SWIZZLE_128B); }

    cudaLaunchConfig_t cfg = {};
    cfg.gridDim = dim3(NCTA); cfg.blockDim = dim3(NTHREADS); cfg.dynamicSmemBytes = SMEM_BYTES;
    cfg.stream = cudaStreamPerThread;
    cudaLaunchAttribute at[2];
    at[0].id = cudaLaunchAttributeClusterDimension;
    at[0].val.clusterDim.x = CLUSTER; at[0].val.clusterDim.y = 1; at[0].val.clusterDim.z = 1;
    at[1].id = cudaLaunchAttributeClusterSchedulingPolicyPreference;
    at[1].val.clusterSchedulingPolicyPreference = cudaClusterSchedulingPolicyLoadBalancing;
    cfg.attrs = at; cfg.numAttrs = 2;
    cudaLaunchKernelEx(&cfg, fused_decode_kernel, m, (const char*)d_in[3], (__nv_bfloat16*)d_out);
}
```

```cpp
#include <cuda_runtime.h>
#include <cuda_bf16.h>
#include <cuda.h>
#include <stdint.h>

namespace {

constexpr int NCTA = 128;
constexpr int CLUSTER = 16;
constexpr int NTHREADS = 288;
constexpr int CHUNK = 16384;
constexpr int NSLOT = 6;
constexpr int NCHUNK = 22;
constexpr int C_K = 3, C_V = 11, C_W2 = 19, C_WO = 20;
#define GATE_K -1
#define GATE_N 14
#define PF_MODE 1
#define KV_HINT 1
#define DEPTH 4
#define PF_BYTES 4096
#define WA 16
#define WB 18
#define WC 18
#define OLOOK 1
#define PROMO_W CU_TENSOR_MAP_L2_PROMOTION_L2_256B
#define EARLY 0
#define W2_NAP 0
constexpr uint32_t SPIN_LIMIT = 1u << 24;

constexpr int RED_PITCH = 36;
constexpr int OFF_RING = 0;
constexpr int OFF_U = NSLOT * CHUNK;
constexpr int OFF_X = OFF_U;
constexpr int OFF_RED = OFF_U;
constexpr int OFF_P = OFF_U;
constexpr int OFF_OB = OFF_U + 4096;
constexpr int OFF_RIN = OFF_U + 9216;
constexpr int OFF_Q = OFF_RIN + 4096;
constexpr int OFF_OST = OFF_Q;
constexpr int OFF_H = OFF_Q + 1024;
constexpr int OFF_ML = OFF_H + 2176;
constexpr int OFF_STAT = OFF_ML + 32;
constexpr int OFF_BAR = OFF_STAT + 336;
constexpr int NBAR = 44;
constexpr int SMEM_BYTES = OFF_BAR + NBAR * 8;
static_assert(2 * (SMEM_BYTES + 1024) <= 233472, "two CTAs per SM");

struct Maps { CUtensorMap x, wq, k, v, w1, wo, w2; };

__device__ unsigned int g_epoch;
__device__ __align__(128) uint32_t g_o[2 * 8 * 32 * 64];
__device__ __align__(128) uint32_t g_h[8 * 896];

#define TSTAMP(idx) do { } while (0)
#define PSTAMP(idx) do { } while (0)

__device__ __forceinline__ uint32_t smem_u32(const void* p) { return (uint32_t)__cvta_generic_to_shared(p); }
__device__ __forceinline__ void mbar_init(uint32_t bar, uint32_t cnt) {
    asm volatile("mbarrier.init.shared::cta.b64 [%0], %1;" :: "r"(bar), "r"(cnt) : "memory");
}
__device__ __forceinline__ void mbar_expect(uint32_t bar, uint32_t bytes) {
    asm volatile("mbarrier.arrive.expect_tx.shared::cta.b64 _, [%0], %1;" :: "r"(bar), "r"(bytes) : "memory");
}
__device__ __forceinline__ void mbar_arrive(uint32_t bar) {
    asm volatile("mbarrier.arrive.shared::cta.b64 _, [%0];" :: "r"(bar) : "memory");
}
__device__ __forceinline__ void mbar_wait(uint32_t bar) {
    uint32_t done;
    for (uint32_t it = 0; ; ++it) {
        asm volatile("{\n.reg .pred p;\nmbarrier.try_wait.parity.shared::cta.b64 p, [%1], 0;\nselp.u32 %0, 1, 0, p;\n}"
                     : "=r"(done) : "r"(bar) : "memory");
        if (done) break;
        if (it > SPIN_LIMIT) __trap();
    }
}
__device__ __forceinline__ bool mbar_test(uint32_t bar) {
    uint32_t done;
    asm volatile("{\n.reg .pred p;\nmbarrier.test_wait.parity.shared::cta.b64 p, [%1], 0;\nselp.u32 %0, 1, 0, p;\n}"
                 : "=r"(done) : "r"(bar) : "memory");
    return done;
}
__device__ __forceinline__ bool mbar_try_ns(uint32_t bar, uint32_t ns) {
    uint32_t done;
    asm volatile("{\n.reg .pred p;\nmbarrier.try_wait.parity.shared::cta.b64 p, [%1], 0, %2;\nselp.u32 %0, 1, 0, p;\n}"
                 : "=r"(done) : "r"(bar), "r"(ns) : "memory");
    return done;
}
__device__ __forceinline__ uint32_t mapa(uint32_t addr, uint32_t rank) {
    uint32_t r; asm("mapa.shared::cluster.u32 %0, %1, %2;" : "=r"(r) : "r"(addr), "r"(rank)); return r;
}
__device__ __forceinline__ void st_async2(uint32_t dst, uint32_t a, uint32_t b, uint32_t bar) {
    asm volatile("st.async.weak.shared::cluster.mbarrier::complete_tx::bytes.v2.b32 [%0], {%1,%2}, [%3];"
                 :: "r"(dst), "r"(a), "r"(b), "r"(bar) : "memory");
}
__device__ __forceinline__ void st_async4(uint32_t dst, uint32_t a, uint32_t b, uint32_t c, uint32_t d, uint32_t bar) {
    asm volatile("st.async.weak.shared::cluster.mbarrier::complete_tx::bytes.v4.b32 [%0], {%1,%2,%3,%4}, [%5];"
                 :: "r"(dst), "r"(a), "r"(b), "r"(c), "r"(d), "r"(bar) : "memory");
}
__device__ __forceinline__ void tma2d(uint32_t dst, const CUtensorMap* m, int c0, int c1, uint32_t bar) {
    asm volatile("cp.async.bulk.tensor.2d.shared::cluster.global.mbarrier::complete_tx::bytes [%0], [%1, {%3, %4}], [%2];"
                 :: "r"(dst), "l"(m), "r"(bar), "r"(c0), "r"(c1) : "memory");
}
__device__ __forceinline__ void tma3d(uint32_t dst, const CUtensorMap* m, int c0, int c1, int c2, uint32_t bar) {
    asm volatile("cp.async.bulk.tensor.3d.shared::cluster.global.mbarrier::complete_tx::bytes [%0], [%1, {%3, %4, %5}], [%2];"
                 :: "r"(dst), "l"(m), "r"(bar), "r"(c0), "r"(c1), "r"(c2) : "memory");
}
__device__ __forceinline__ void tma3d_hint(uint32_t dst, const CUtensorMap* m, int c0, int c1, int c2, uint32_t bar, uint64_t pol) {
    asm volatile("cp.async.bulk.tensor.3d.shared::cluster.global.mbarrier::complete_tx::bytes.L2::cache_hint [%0], [%1, {%3, %4, %5}], [%2], %6;"
                 :: "r"(dst), "l"(m), "r"(bar), "r"(c0), "r"(c1), "r"(c2), "l"(pol) : "memory");
}
__device__ __forceinline__ void l2_prefetch(const void* src, uint32_t bytes) {
    asm volatile("cp.async.bulk.prefetch.L2.global [%0], %1;" :: "l"(src), "r"(bytes) : "memory");
}
__device__ __forceinline__ void ldsm4(uint32_t (&r)[4], uint32_t addr) {
    asm volatile("ldmatrix.sync.aligned.m8n8.x4.shared.b16 {%0,%1,%2,%3}, [%4];"
                 : "=r"(r[0]), "=r"(r[1]), "=r"(r[2]), "=r"(r[3]) : "r"(addr) : "memory");
}
__device__ __forceinline__ void ldsm4t(uint32_t (&r)[4], uint32_t addr) {
    asm volatile("ldmatrix.sync.aligned.m8n8.x4.trans.shared.b16 {%0,%1,%2,%3}, [%4];"
                 : "=r"(r[0]), "=r"(r[1]), "=r"(r[2]), "=r"(r[3]) : "r"(addr) : "memory");
}
__device__ __forceinline__ void mma16816(float (&d)[4], const uint32_t (&a)[4], uint32_t b0, uint32_t b1) {
    asm volatile("mma.sync.aligned.m16n8k16.row.col.f32.bf16.bf16.f32 {%0,%1,%2,%3}, {%4,%5,%6,%7}, {%8,%9}, {%0,%1,%2,%3};"
                 : "+f"(d[0]), "+f"(d[1]), "+f"(d[2]), "+f"(d[3])
                 : "r"(a[0]), "r"(a[1]), "r"(a[2]), "r"(a[3]), "r"(b0), "r"(b1));
}
__device__ __forceinline__ uint32_t movtrans(uint32_t a) {
    uint32_t d;
    asm volatile("movmatrix.sync.aligned.m8n8.trans.b16 %0, %1;" : "=r"(d) : "r"(a));
    return d;
}
__device__ __forceinline__ uint32_t pack_bf16(float lo, float hi) {
    uint32_t d;
    asm("cvt.rn.bf16x2.f32 %0, %1, %2;" : "=r"(d) : "f"(hi), "f"(lo));
    return d;
}
__device__ __forceinline__ float bf16r(float x) { return __bfloat162float(__float2bfloat16_rn(x)); }
__device__ __forceinline__ float bf_lo(uint32_t u) { return __uint_as_float(u << 16); }
__device__ __forceinline__ float bf_hi(uint32_t u) { return __uint_as_float(u & 0xffff0000u); }
__device__ __forceinline__ uint32_t hadd2_bf16(uint32_t a, uint32_t b) {
    uint32_t d;
    asm("add.rn.bf16x2 %0, %1, %2;" : "=r"(d) : "r"(a), "r"(b));
    return d;
}
__device__ __forceinline__ uint32_t ld_rlx(const uint32_t* p) {
    uint32_t v; asm volatile("ld.relaxed.gpu.global.u32 %0, [%1];" : "=r"(v) : "l"(p) : "memory"); return v;
}
__device__ __forceinline__ uint4 ld_rlx_2x64(const void* p) {
    unsigned long long a, b;
    asm volatile("ld.relaxed.gpu.global.v2.b64 {%0,%1}, [%2];" : "=l"(a), "=l"(b) : "l"(p) : "memory");
    return make_uint4((uint32_t)a, (uint32_t)(a >> 32), (uint32_t)b, (uint32_t)(b >> 32));
}
__device__ __forceinline__ void st_rlx_2x64(void* p, const uint4& v) {
    asm volatile("st.relaxed.gpu.global.v2.b64 [%0], {%1,%2};" :: "l"(p),
                 "l"(((unsigned long long)v.y << 32) | v.x), "l"(((unsigned long long)v.w << 32) | v.z) : "memory");
}
__device__ __forceinline__ void st_rlx_64(void* p, uint32_t lo, uint32_t hi) {
    asm volatile("st.relaxed.gpu.global.b64 [%0], %1;" :: "l"(p), "l"(((unsigned long long)hi << 32) | lo) : "memory");
}
__device__ __forceinline__ bool tagged(const uint4& v, uint32_t tag) { return (((v.x ^ tag) | (v.z ^ tag)) & 1u) == 0u; }
__device__ __forceinline__ void st_rlx(uint32_t* p, uint32_t v) {
    asm volatile("st.relaxed.gpu.global.u32 [%0], %1;" :: "l"(p), "r"(v) : "memory");
}
template <typename T> __device__ __forceinline__ void pin64(T*& p) { asm volatile("" : "+l"(p)); }
__device__ __forceinline__ void pin32(uint32_t& v) { asm volatile("" : "+r"(v)); }
__device__ __forceinline__ void cbar() { asm volatile("bar.sync 1, 256;" ::: "memory"); }
__device__ __forceinline__ float ex2(float x) { float y; asm("ex2.approx.ftz.f32 %0, %1;" : "=f"(y) : "f"(x)); return y; }

__global__ void __launch_bounds__(NTHREADS, 2)
fused_decode_kernel(const __grid_constant__ Maps maps, const char* __restrict__ wq_raw, __nv_bfloat16* __restrict__ out,
                    const char* __restrict__ k_raw, const char* __restrict__ v_raw, const char* __restrict__ wo_raw,
                    const char* __restrict__ w1_raw, const char* __restrict__ w2_raw)
{
    extern __shared__ __align__(1024) char smp[];
    const uint32_t sm = smem_u32(smp);
    const int tid = threadIdx.x, warp = tid >> 5, lane = tid & 31;
    const int cta = blockIdx.x, g = cta >> 4, c = cta & 15, b = c >> 1, half = c & 1;
    const bool ffn = g < 7;
    const uint32_t bar_full = sm + OFF_BAR, bar_empty = bar_full + NCHUNK * 8;
    const uint32_t bar_q = bar_empty + 16 * 8, bar_ml = bar_q + 8, bar_r = bar_q + 16, bar_x = bar_q + 24, bar_g = bar_q + 32, bar_ob = bar_q + 40;

    if (warp == 8) {
        if (lane == 0) {
            if (PF_BYTES && !(PF_MODE & 1)) l2_prefetch(wq_raw + (size_t)cta * 32768, PF_BYTES);
            mbar_init(bar_x, 1); mbar_init(bar_full, 1); mbar_init(bar_full + 8, 1);
            asm volatile("fence.proxy.async.shared::cta;" ::: "memory");
            mbar_expect(bar_x, 8192); tma3d(sm + OFF_X, &maps.x, 0, 0, 0, bar_x);
            mbar_expect(bar_full, CHUNK); tma2d(sm, &maps.wq, cta * 32, 0, bar_full);
            mbar_expect(bar_full + 8, CHUNK); tma2d(sm + CHUNK, &maps.wq, cta * 32, 256, bar_full + 8);
            if (sm & 1023u) __trap();
            #pragma unroll
            for (int s = 2; s < NCHUNK; s++) mbar_init(bar_full + s * 8, 1);
            #pragma unroll
            for (int s = 0; s < 16; s++) mbar_init(bar_empty + s * 8, s < 2 ? 4 : (s >= C_K && s < C_V) ? 1 : 8);
            #pragma unroll
            for (int s = 0; s < 3; s++) mbar_init(bar_q + s * 8, 1);
            mbar_init(bar_g, GATE_N); mbar_init(bar_ob, 8);
            mbar_expect(bar_q, 1024); mbar_expect(bar_ml, 32); mbar_expect(bar_r, 4096);
            asm volatile("fence.mbarrier_init.release.cluster;" ::: "memory");
            asm volatile("fence.proxy.async.shared::cta;" ::: "memory");
        }
        __syncwarp();
        asm volatile("barrier.cluster.arrive.relaxed.aligned;" ::: "memory");
        asm volatile("bar.arrive 2, %0;" :: "n"(NTHREADS) : "memory");
        if (lane == 0) {
            TSTAMP(33);
            if (EARLY) { }
            else if (ffn) {
                mbar_expect(bar_full + 16, CHUNK);
                tma2d(sm + 2 * CHUNK, &maps.w1, cta * 16, 0, bar_full + 16);
                tma2d(sm + 2 * CHUNK + 8192, &maps.w1, cta * 16, 256, bar_full + 16);
            } else mbar_arrive(bar_full + 16);
            const int row0 = (b * 8 + g) * 4096 + 3072 + half * 512;
            uint32_t dst = sm + C_K * CHUNK;
            #pragma unroll 1
            for (int ch = C_K; ch < NCHUNK; ch++) {
                if (ch >= DEPTH) mbar_wait(bar_full + (ch < C_W2 ? ch - DEPTH : ch == C_W2 ? WA : ch == C_WO ? WB : WC) * 8);
                if (ch >= NSLOT) mbar_wait(bar_empty + (ch - NSLOT) * 8);
                if (GATE_K >= 0 && ch == C_W2) mbar_wait(bar_g);
                const uint32_t bar = bar_full + ch * 8;
                if (ch < C_W2) {
                    mbar_expect(bar, CHUNK);
                    uint64_t pol;
                    asm volatile("createpolicy.fractional.L2::evict_first.b64 %0, 1.0;" : "=l"(pol));
                    tma3d_hint(dst, ch < C_V ? &maps.k : &maps.v, 0, row0 + ((ch - C_K) & 7) * 64, 0, bar, pol);
                } else {
                    mbar_expect(bar, ch == C_W2 ? 14336 : CHUNK);
                    tma2d(dst, ch == C_W2 ? &maps.w2 : &maps.wo, g * 64,
                          ch == C_W2 ? c * 112 : c * 256 + (ch - C_WO) * 128, bar);
                }
                dst = (dst == sm + (NSLOT - 1) * CHUNK) ? sm : dst + CHUNK;
                TSTAMP(32 + ch);
            }
        }
        __syncwarp();
        asm volatile("barrier.cluster.wait.aligned;" ::: "memory");
        return;
    }

    if (tid == 0) {
        const size_t kvo = ((size_t)(b * 8 + g) * 4096 + 3072 + half * 512) * 256;
        if ((PF_MODE & 1) && !EARLY) l2_prefetch(wq_raw + (size_t)cta * 32768, PF_BYTES);
        if (PF_MODE & 2) { l2_prefetch(k_raw + kvo, 128); l2_prefetch(v_raw + kvo, 128); l2_prefetch(wo_raw + (size_t)cta * 32768, 128);
                           l2_prefetch(w2_raw + (size_t)cta * 14336, 128); l2_prefetch(w1_raw + (size_t)cta * 14336, 128); }
        if (PF_MODE & 4) l2_prefetch(k_raw + kvo, 8192);
        if (PF_MODE & 8) l2_prefetch(w1_raw + (size_t)cta * 14336, 14336);
        if (PF_MODE & 16) l2_prefetch(k_raw + kvo, 16384);
    }
    if ((PF_MODE & 32) && tid == 32) {
        asm volatile("prefetch.tensormap [%0];" :: "l"(&maps.x) : "memory");
        asm volatile("prefetch.tensormap [%0];" :: "l"(&maps.wq) : "memory");
        asm volatile("prefetch.tensormap [%0];" :: "l"(&maps.w1) : "memory");
        asm volatile("prefetch.tensormap [%0];" :: "l"(&maps.k) : "memory");
    }
    if ((PF_MODE & 64) && tid == 64) {
        asm volatile("prefetch.tensormap [%0];" :: "l"(&maps.v) : "memory");
        asm volatile("prefetch.tensormap [%0];" :: "l"(&maps.wo) : "memory");
        asm volatile("prefetch.tensormap [%0];" :: "l"(&maps.w2) : "memory");
    }
    asm volatile("barrier.cluster.arrive.relaxed.aligned;" ::: "memory");
    const int gl = lane >> 2, t = lane & 3;
    float* lnst = reinterpret_cast<float*>(smp + OFF_STAT + 256);
    volatile uint32_t* epoch_s = reinterpret_cast<volatile uint32_t*>(smp + OFF_STAT + 320);
    const int ru = lane & 7, rp = lane >> 3;
    const int ob = 2 * (ru & 3) + (rp & 1);
    const int ocol = g * 64 + (c >> 2) * 16 + 2 * (c & 3) + (ru >> 2) + 8 * (rp >> 1);
    uint32_t epoch_r = 0;
    if (tid == 64) epoch_r = ld_rlx(&g_epoch);
    asm volatile("bar.sync 2, %0;" :: "n"(NTHREADS) : "memory");
    if (tid == 64) *epoch_s = epoch_r;
    mbar_wait(bar_x);
    if (tid == 0) TSTAMP(5);
    uint32_t xf[8];
    #pragma unroll
    for (int j = 0; j < 8; j++)
        xf[j] = *reinterpret_cast<const uint32_t*>(smp + OFF_X + warp * 1024 + gl * 128 + ((j ^ gl) << 4) + t * 4);
    const float resid = __bfloat162float(*reinterpret_cast<const __nv_bfloat16*>(
        smp + OFF_X + g * 1024 + ob * 128 + ((((ocol >> 3) & 7) ^ ob) << 4) + (ocol & 7) * 2));
    {
        const char* xr = smp + OFF_X + (lane >> 3) * 1024 + warp * 128 + (lane & 7) * 16;
        const uint4 xa = *reinterpret_cast<const uint4*>(xr), xb = *reinterpret_cast<const uint4*>(xr + 4096);
        const float sh = bf_lo(*reinterpret_cast<const uint32_t*>(smp + OFF_X + warp * 128));
        const uint32_t w[8] = {xa.x, xa.y, xa.z, xa.w, xb.x, xb.y, xb.z, xb.w};
        float s4[4] = {}, q4[4] = {};
        #pragma unroll
        for (int j = 0; j < 8; j++) {
            const float lo = bf_lo(w[j]) - sh, hi = bf_hi(w[j]) - sh;
            s4[j & 3] += lo + hi;
            q4[j & 3] = fmaf(lo, lo, fmaf(hi, hi, q4[j & 3]));
        }
        float s = (s4[0] + s4[1]) + (s4[2] + s4[3]), q2 = (q4[0] + q4[1]) + (q4[2] + q4[3]);
        #pragma unroll
        for (int o = 16; o > 0; o >>= 1) {
            s += __shfl_xor_sync(0xffffffffu, s, o);
            q2 += __shfl_xor_sync(0xffffffffu, q2, o);
        }
        const float ms = s * (1.f / 512.f), mean = sh + ms;
        q2 = fmaxf(fmaf(-ms, s, q2), 0.f);
        const float den = bf16r(__fsqrt_rn(bf16r(bf16r(q2 * (1.f / 512.f)) + 1e-5f)));
        if (lane == 0) *reinterpret_cast<float2*>(lnst + warp * 2) = make_float2(bf16r(mean), __frcp_rn(den));
    }
    cbar();
    {
        const float2 st = *reinterpret_cast<const float2*>(lnst + gl * 2);
        #pragma unroll
        for (int j = 0; j < 8; j++)
            xf[j] = pack_bf16(bf16r(bf_lo(xf[j]) - st.x) * st.y, bf16r(bf_hi(xf[j]) - st.x) * st.y);
    }
    const uint32_t tag = (*epoch_s + 1u) & 1u;
    if (tid == 0) TSTAMP(1);

    float* red = reinterpret_cast<float*>(smp + OFF_RED);
    const int mj = lane >> 3, mr = lane & 7;
    float* r0 = red + (warp * 8 + 2 * t) * RED_PITCH + gl;
    {
        float aq[2][4] = {};
        mbar_wait(bar_full + (warp >> 2) * 8);
        const uint32_t wqs = sm + OFF_RING + (warp >> 2) * CHUNK;
        #pragma unroll
        for (int s = 0; s < 4; s++) {
            const int row = (warp & 3) * 64 + s * 16 + (mj >> 1) * 8 + mr;
            #pragma unroll
            for (int j = 0; j < 2; j++) {
                uint32_t a[4];
                ldsm4t(a, wqs + row * 64 + (((2 * j + (mj & 1)) ^ ((row >> 1) & 3)) << 4));
                mma16816(aq[j], a, xf[2 * s], xf[2 * s + 1]);
            }
        }
        __syncwarp();
        if (lane == 0) mbar_arrive(bar_empty + (warp >> 2) * 8);
        #pragma unroll
        for (int j = 0; j < 2; j++) {
            r0[j * 16] = aq[j][0]; r0[RED_PITCH + j * 16] = aq[j][1];
            r0[j * 16 + 8] = aq[j][2]; r0[RED_PITCH + j * 16 + 8] = aq[j][3];
        }
    }
    cbar();
    asm volatile("barrier.cluster.wait.aligned;" ::: "memory");
    if (warp < 4) {
        const int bb = tid >> 4, wd = tid & 15;
        const int col = (wd >> 3) * 16 + ((wd >> 1) & 3) * 2 + (wd & 1) * 8;
        float s0 = 0.f, s1 = 0.f;
        #pragma unroll
        for (int w = 0; w < 8; w++) {
            const float2 f = *reinterpret_cast<const float2*>(red + (w * 8 + bb) * RED_PITCH + col);
            s0 += f.x; s1 += f.y;
        }
        const uint32_t u = pack_bf16(s0, s1);
        const int q0 = (lane & 16) + (lane & 3) * 4;
        const uint32_t u0 = __shfl_sync(0xffffffffu, u, q0), u1 = __shfl_sync(0xffffffffu, u, q0 + 1);
        const uint32_t u2 = __shfl_sync(0xffffffffu, u, q0 + 2), u3 = __shfl_sync(0xffffffffu, u, q0 + 3);
        if (wd < 8) {
            const uint32_t rank = 2 * bb + (wd >> 2);
            st_async4(mapa(sm + OFF_Q + c * 64 + (wd & 3) * 16, rank), u0, u1, u2, u3, mapa(bar_q, rank));
        }
    }
    if (tid == 0) TSTAMP(2);
    if (ffn) {
        float ah[4] = {};
        mbar_wait(bar_full + 2 * 8);
        const uint32_t w1s = sm + OFF_RING + 2 * CHUNK;
        #pragma unroll
        for (int s = 0; s < 4; s++) {
            const int row = warp * 64 + s * 16 + (mj >> 1) * 8 + mr;
            uint32_t a[4];
            ldsm4t(a, w1s + row * 32 + (((mj & 1) ^ ((row >> 2) & 1)) << 4));
            mma16816(ah, a, xf[2 * s], xf[2 * s + 1]);
        }
        __syncwarp();
        if (lane == 0) mbar_arrive(bar_empty + 2 * 8);
        cbar();
        r0[0] = ah[0]; r0[RED_PITCH] = ah[1]; r0[8] = ah[2]; r0[RED_PITCH + 8] = ah[3];
        cbar();
        if (warp >= 6) {
            const int bb = (tid & 63) >> 3, wd = tid & 7;
            float s0 = 0.f, s1 = 0.f;
            #pragma unroll
            for (int w = 0; w < 8; w++) {
                const float2 f = *reinterpret_cast<const float2*>(red + (w * 8 + bb) * RED_PITCH + 2 * wd);
                s0 += f.x; s1 += f.y;
            }
            s0 = bf16r(s0); s1 = bf16r(s1);
            s0 = __fdividef(s0, 1.f + __expf(-s0)); s1 = __fdividef(s1, 1.f + __expf(-s1));
            const uint32_t u = pack_bf16(s0, s1);
            const uint32_t un = __shfl_down_sync(0xffffffffu, u, 1);
            if (!(wd & 1)) st_rlx_64(g_h + bb * 896 + cta * 8 + wd, (u & ~1u) | tag, un);
        }
    } else {
        __syncwarp();
        if (lane == 0) mbar_arrive(bar_empty + 2 * 8);
    }
    if (tid == 0) TSTAMP(22);

    float sc[4][4];
    {
        mbar_wait(bar_q);
        if (tid == 0) TSTAMP(3);
        uint32_t qb[8][2];
        #pragma unroll
        for (int s = 0; s < 8; s++) {
            const uint2 v = *reinterpret_cast<const uint2*>(smp + OFF_Q + (((gl & 3) * 8 + s) * 4 + t) * 8);
            qb[s][0] = v.x; qb[s][1] = v.y;
        }
        mbar_wait(bar_full + (C_K + warp) * 8);
        const uint32_t ks = sm + OFF_RING + ((C_K + warp) % NSLOT) * CHUNK;
        #pragma unroll
        for (int i = 0; i < 4; i++) { sc[i][0] = sc[i][1] = sc[i][2] = sc[i][3] = 0.f; }
        #pragma unroll
        for (int s = 0; s < 8; s++) {
            const int ch = 2 * s + (mj >> 1);
            #pragma unroll
            for (int i = 0; i < 4; i++) {
                const int row = i * 16 + (mj & 1) * 8 + mr;
                uint32_t a[4];
                ldsm4(a, ks + (ch >> 3) * 8192 + row * 128 + (((ch & 7) ^ mr) << 4));
                mma16816(sc[i], a, qb[s][0], qb[s][1]);
            }
        }
        __syncwarp();
        if (lane == 0) mbar_arrive(bar_empty + (C_K + warp) * 8);
    }
    float* wmax = reinterpret_cast<float*>(smp + OFF_STAT);
    float* wsum = wmax + 32;
    float m0, m1;
    constexpr float L2E = 1.4426950408889634f;
    {
        m0 = -INFINITY; m1 = -INFINITY;
        #pragma unroll
        for (int i = 0; i < 4; i++) {
            #pragma unroll
            for (int k = 0; k < 4; k++) sc[i][k] = bf16r(bf16r(sc[i][k]) * 0.08838834764831845f);
            m0 = fmaxf(m0, fmaxf(sc[i][0], sc[i][2]));
            m1 = fmaxf(m1, fmaxf(sc[i][1], sc[i][3]));
        }
        #pragma unroll
        for (int o = 4; o < 32; o <<= 1) {
            m0 = fmaxf(m0, __shfl_xor_sync(0xffffffffu, m0, o));
            m1 = fmaxf(m1, __shfl_xor_sync(0xffffffffu, m1, o));
        }
        if (lane < 2) *reinterpret_cast<float2*>(wmax + warp * 4 + 2 * lane) = make_float2(m0, m1);
        cbar();
        #pragma unroll
        for (int w = 0; w < 8; w++) {
            const float2 f = *reinterpret_cast<const float2*>(wmax + w * 4 + 2 * (t & 1));
            m0 = fmaxf(m0, f.x); m1 = fmaxf(m1, f.y);
        }
        float l0 = 0.f, l1 = 0.f;
        uint32_t pw[4][2];
        #pragma unroll
        for (int i = 0; i < 4; i++) {
            const float p0 = ex2((sc[i][0] - m0) * L2E), p1 = ex2((sc[i][1] - m1) * L2E);
            const float p2 = ex2((sc[i][2] - m0) * L2E), p3 = ex2((sc[i][3] - m1) * L2E);
            l0 += p0 + p2; l1 += p1 + p3;
            pw[i][0] = movtrans(pack_bf16(p0, p1));
            pw[i][1] = movtrans(pack_bf16(p2, p3));
        }
        if (lane < 16) {
            uint4* pd = reinterpret_cast<uint4*>(smp + OFF_P) + (warp * 2) * 16 + lane;
            pd[0] = make_uint4(pw[0][0], pw[0][1], pw[1][0], pw[1][1]);
            pd[16] = make_uint4(pw[2][0], pw[2][1], pw[3][0], pw[3][1]);
        }
        #pragma unroll
        for (int o = 4; o < 32; o <<= 1) {
            l0 += __shfl_xor_sync(0xffffffffu, l0, o);
            l1 += __shfl_xor_sync(0xffffffffu, l1, o);
        }
        if (lane < 2) *reinterpret_cast<float2*>(wsum + warp * 4 + 2 * lane) = make_float2(l0, l1);
    }
    cbar();
    float l0 = 0.f, l1 = 0.f;
    #pragma unroll
    for (int w = 0; w < 8; w++) {
        const float2 f = *reinterpret_cast<const float2*>(wsum + w * 4 + 2 * (t & 1));
        l0 += f.x; l1 += f.y;
    }
    if (tid < 2) {
        const uint32_t dst = mapa(sm + OFF_ML + tid * 8, c ^ 1), bar = mapa(bar_ml, c ^ 1);
        st_async2(dst, __float_as_uint(m0), __float_as_uint(m1), bar);
        st_async2(dst + 16, __float_as_uint(l0), __float_as_uint(l1), bar);
    }
    if (tid == 0) TSTAMP(4);

    const uint32_t* op = g_o + (((tid >> 4) & 7) * 32 + 2 * c + (tid >> 7)) * 64 + (tid & 15) * 4;
    uint32_t* opub = g_o + ((half * 8 + b) * 32 + g * 4) * 64 + (tid & 63) * 4;
    __nv_bfloat16* outp = out + ob * 512 + ocol;
    uint32_t s_ost = sm + OFF_OST + gl * 256 + (t * 4 + ((warp >> 1) ^ (t & 2))) * 16 + (warp & 1) * 8;
    uint32_t s_rdst = mapa(sm + OFF_RIN + (c * 2 + (warp >> 2)) * 128 + ru * 16, (warp & 3) * 4 + rp);
    uint32_t s_rbar = mapa(bar_r, (warp & 3) * 4 + rp);
    uint32_t s_obw = sm + OFF_OB + (tid >> 4) * 320 + (((tid & 15) ^ ((tid >> 4) & 1)) << 4);
    uint32_t s_obr = sm + OFF_OB + ((warp >> 2) * 8 + gl) * 320 + t * 64 + (((t & 2) ^ (gl & 1)) << 4);
    pin32(s_obw); pin32(s_obr);
    pin64(op); pin64(opub); pin64(outp); pin32(s_ost); pin32(s_rdst); pin32(s_rbar);
    const int hb = min(tid / 14, 7), hpc = tid - (tid / 14) * 14;
    const uint32_t* hp = g_h + hb * 896 + c * 56 + hpc * 4;
    uint32_t s_h = sm + OFF_H + hb * 272 + hpc * 16;
    pin64(hp); pin32(s_h);
    uint4 hv = make_uint4(tag, 0u, tag, 0u);
    if (tid < 112) hv = ld_rlx_2x64(hp);
    uint4 oa = ld_rlx_2x64(op), obv = ld_rlx_2x64(op + 16384);
    float f0 = 0.f, f1 = 0.f;
    float oc[4][4] = {};
    {
        const int ach = 2 * warp + (mj & 1);
        const uint32_t voff = (ach >> 3) * 8192 + ((mj >> 1) * 8 + mr) * 128 + (((ach & 7) ^ mr) << 4);
        const uint4* pfp = reinterpret_cast<const uint4*>(smp + OFF_P) + (lane & 15);
        uint32_t vs = sm + OFF_RING + (C_V % NSLOT) * CHUNK;
        #pragma unroll 1
        for (int j = 0; j < 8; j++) {
            const uint4 pa = pfp[j * 32], pb = pfp[j * 32 + 16];
            if (j == 6) {
                for (uint32_t it = 0; !tagged(hv, tag); ++it) {
                    hv = ld_rlx_2x64(hp);
                    if (it > SPIN_LIMIT) __trap();
                }
                if (tid < 112)
                    asm volatile("st.shared.v4.b32 [%0], {%1,%2,%3,%4};" :: "r"(s_h), "r"(hv.x), "r"(hv.y), "r"(hv.z), "r"(hv.w) : "memory");
                __syncwarp();
                mbar_wait(bar_ml);
                const float* pm = reinterpret_cast<const float*>(smp + OFF_ML) + (t & 1) * 2;
                const float mo0 = pm[0], mo1 = pm[1];
                const float mt0 = fmaxf(m0, mo0), mt1 = fmaxf(m1, mo1);
                const float e0 = ex2((m0 - mt0) * L2E), e1 = ex2((m1 - mt1) * L2E);
                f0 = __fdividef(e0, l0 * e0 + pm[4] * ex2((mo0 - mt0) * L2E));
                f1 = __fdividef(e1, l1 * e1 + pm[5] * ex2((mo1 - mt1) * L2E));
            }
            mbar_wait(bar_full + (C_V + j) * 8);
            if (tid == 0) TSTAMP(8 + j);
            if (j == GATE_K && tid >= 240)
                asm volatile("mbarrier.arrive.relaxed.cluster.shared::cluster.b64 _, [%0];" :: "r"(mapa(bar_g, tid & 15)) : "memory");
            uint32_t a[4][4];
            #pragma unroll
            for (int s = 0; s < 4; s++) ldsm4t(a[s], vs + voff + s * 2048);
            mma16816(oc[0], a[0], pa.x, pa.y);
            mma16816(oc[1], a[1], pa.z, pa.w);
            mma16816(oc[2], a[2], pb.x, pb.y);
            mma16816(oc[3], a[3], pb.z, pb.w);
            __syncwarp();
            if (j < 5 && lane == 0) mbar_arrive(bar_empty + (C_V + j) * 8);
            vs = (vs == sm + (NSLOT - 1) * CHUNK) ? sm : vs + CHUNK;
        }
    }
    {
        const float o0 = (oc[0][0] + oc[1][0]) + (oc[2][0] + oc[3][0]);
        const float o1 = (oc[0][1] + oc[1][1]) + (oc[2][1] + oc[3][1]);
        const float o2 = (oc[0][2] + oc[1][2]) + (oc[2][2] + oc[3][2]);
        const float o3 = (oc[0][3] + oc[1][3]) + (oc[2][3] + oc[3][3]);
        const uint32_t u0 = movtrans(pack_bf16(o0 * f0, o1 * f1));
        const uint32_t u1 = movtrans(pack_bf16(o2 * f0, o3 * f1));
        if (lane < 16)
            asm volatile("st.shared.v2.b32 [%0], {%1,%2};" :: "r"(s_ost), "r"((u0 & ~1u) | tag), "r"(u1) : "memory");
        cbar();
        if (tid < 64) st_rlx_2x64(opub, *reinterpret_cast<const uint4*>(smp + OFF_OST + tid * 16));
        pin32(oa.x); pin32(oa.z); pin32(obv.x); pin32(obv.z);
    }
    if (tid == 0) TSTAMP(16);

    {
        const int mt = warp & 3, kh = warp >> 2;
        const uint32_t aoff = ((mj >> 1) * 8 + mr) * 128 + (((2 * mt + (mj & 1)) ^ mr) << 4);
        float ac[4][4] = {};
        const uint32_t* hs = reinterpret_cast<const uint32_t*>(smp + OFF_H) + gl * 68 + kh * 32 + t;
        const uint32_t w2s = sm + OFF_RING + (C_W2 % NSLOT) * CHUNK + kh * 8192 + aoff;
        auto ffn_part = [&]() {
            #pragma unroll
            for (int s = 0; s < 4; s++) {
                if (s < 3 || kh == 0) {
                    uint32_t a[4];
                    ldsm4t(a, w2s + s * 2048);
                    mma16816(ac[s], a, hs[s * 8], hs[s * 8 + 4]);
                }
            }
        };
        const uint32_t wos = sm + OFF_RING + ((C_WO % NSLOT) + kh) * CHUNK + aoff;
        const uint32_t bar_wo = bar_full + (C_WO + kh) * 8;
        uint32_t wa[8][4];
        bool have_w2 = false, have_wo = false;
        for (uint32_t it = 0; ; ++it) {
            const bool na = !tagged(oa, tag), nb = !tagged(obv, tag);
            if (!__any_sync(0xffffffffu, na || nb)) break;
            if (W2_NAP && it && !have_w2) mbar_try_ns(bar_full + C_W2 * 8, W2_NAP);
            if (na) oa = ld_rlx_2x64(op);
            if (nb) obv = ld_rlx_2x64(op + 16384);
            if (!have_w2 && mbar_test(bar_full + C_W2 * 8)) { have_w2 = true; ffn_part(); }
            if (!have_wo && mbar_test(bar_wo)) {
                have_wo = true;
                #pragma unroll
                for (int s = 0; s < 8; s++) ldsm4t(wa[s], wos + s * 2048);
            }
            if (it > SPIN_LIMIT) __trap();
        }
        asm volatile("st.shared.v4.b32 [%0], {%1,%2,%3,%4};" :: "r"(s_obw), "r"(hadd2_bf16(oa.x, obv.x)),
                     "r"(hadd2_bf16(oa.y, obv.y)), "r"(hadd2_bf16(oa.z, obv.z)), "r"(hadd2_bf16(oa.w, obv.w)) : "memory");
        __syncwarp();
        if (lane == 0) mbar_arrive(bar_ob);
        if (!have_w2) { mbar_wait(bar_full + C_W2 * 8); ffn_part(); }
        if (!have_wo && mbar_test(bar_wo)) {
            have_wo = true;
            #pragma unroll
            for (int s = 0; s < 8; s++) ldsm4t(wa[s], wos + s * 2048);
        }
        mbar_wait(bar_ob);
        if (tid == 0) TSTAMP(17);
        uint4 of[4];
        #pragma unroll
        for (int s2 = 0; s2 < 4; s2++)
            asm volatile("ld.shared.v4.b32 {%0,%1,%2,%3}, [%4];" : "=r"(of[s2].x), "=r"(of[s2].y), "=r"(of[s2].z), "=r"(of[s2].w)
                         : "r"(s_obr ^ (s2 << 4)) : "memory");
        if (!have_wo) {
            mbar_wait(bar_wo);
            #pragma unroll
            for (int s = 0; s < 8; s++) ldsm4t(wa[s], wos + s * 2048);
        }
        if (tid == 128) TSTAMP(25);
        #pragma unroll
        for (int s2 = 0; s2 < 4; s2++) {
            mma16816(ac[(2 * s2) & 3], wa[2 * s2], of[s2].x, of[s2].y);
            mma16816(ac[(2 * s2 + 1) & 3], wa[2 * s2 + 1], of[s2].z, of[s2].w);
        }
        st_async4(s_rdst,
                  __float_as_uint((ac[0][0] + ac[1][0]) + (ac[2][0] + ac[3][0])),
                  __float_as_uint((ac[0][1] + ac[1][1]) + (ac[2][1] + ac[3][1])),
                  __float_as_uint((ac[0][2] + ac[1][2]) + (ac[2][2] + ac[3][2])),
                  __float_as_uint((ac[0][3] + ac[1][3]) + (ac[2][3] + ac[3][3])), s_rbar);
    }
    if (tid == 128) TSTAMP(19);

    if (warp == 0) {
        mbar_wait(bar_r);
        if (tid == 0) TSTAMP(27);
        float s0 = 0.f, s1 = 0.f, s2 = 0.f, s3 = 0.f;
        #pragma unroll
        for (int i = 0; i < 8; i++) {
            const float4 v = *reinterpret_cast<const float4*>(smp + OFF_RIN + (i * 4 + rp) * 128 + ru * 16);
            s0 += v.x; s1 += v.y; s2 += v.z; s3 += v.w;
        }
        float a = (rp & 1) ? s1 : s0, bq = (rp & 1) ? s3 : s2;
        a += __shfl_xor_sync(0xffffffffu, (rp & 1) ? s0 : s1, 8);
        bq += __shfl_xor_sync(0xffffffffu, (rp & 1) ? s2 : s3, 8);
        float r = (rp & 2) ? bq : a;
        r += __shfl_xor_sync(0xffffffffu, (rp & 2) ? a : bq, 16);
        *outp = __float2bfloat16_rn(r + resid);
        if (cta == 0 && lane == 0) st_rlx(&g_epoch, *epoch_s + 1u);
        if (lane == 0) PSTAMP(20);
    }
}

typedef CUresult (*EncodeFn)(CUtensorMap*, CUtensorMapDataType, cuuint32_t, void*, const cuuint64_t*, const cuuint64_t*,
                             const cuuint32_t*, const cuuint32_t*, CUtensorMapInterleave, CUtensorMapSwizzle,
                             CUtensorMapL2promotion, CUtensorMapFloatOOBfill);

void encode(EncodeFn fn, CUtensorMap* m, const void* p, int rank, const cuuint64_t* dims, const cuuint64_t* strides,
            const cuuint32_t* box, CUtensorMapSwizzle sw,
            CUtensorMapL2promotion promo = CU_TENSOR_MAP_L2_PROMOTION_L2_256B) {
    const cuuint32_t es[3] = {1, 1, 1};
    fn(m, CU_TENSOR_MAP_DATA_TYPE_BFLOAT16, rank, const_cast<void*>(p), dims, strides, box, es,
       CU_TENSOR_MAP_INTERLEAVE_NONE, sw, promo, CU_TENSOR_MAP_FLOAT_OOB_FILL_NONE);
}

}

extern "C" void kernel_launch(void* const* d_in, const int* in_sizes, int n_in, void* d_out, int out_size) {
    (void)in_sizes; (void)n_in; (void)out_size;
    static EncodeFn fn = nullptr;
    if (!fn) {
        cudaDriverEntryPointQueryResult qr;
        cudaGetDriverEntryPoint("cuTensorMapEncodeTiled", (void**)&fn, cudaEnableDefault, &qr);
        cudaFuncSetAttribute(fused_decode_kernel, cudaFuncAttributeMaxDynamicSharedMemorySize, SMEM_BYTES);
        cudaFuncSetAttribute(fused_decode_kernel, cudaFuncAttributeNonPortableClusterSizeAllowed, 1);
    }
    Maps m;
    {
        const cuuint64_t d[3] = {64, 64ull * 4096, 2}, s[2] = {256, 128};
        const cuuint32_t bx[3] = {64, 64, 2};
        encode(fn, &m.k, d_in[1], 3, d, s, bx, CU_TENSOR_MAP_SWIZZLE_128B);
        encode(fn, &m.v, d_in[2], 3, d, s, bx, CU_TENSOR_MAP_SWIZZLE_128B);
    }
    { const cuuint64_t d[3] = {64, 8, 8}, s[2] = {1024, 128}; const cuuint32_t bx[3] = {64, 8, 8};
      encode(fn, &m.x, d_in[0], 3, d, s, bx, CU_TENSOR_MAP_SWIZZLE_128B); }
    { const cuuint64_t d[2] = {4096, 512}, s[1] = {8192}; const cuuint32_t bx[2] = {32, 256};
      encode(fn, &m.wq, d_in[3], 2, d, s, bx, CU_TENSOR_MAP_SWIZZLE_64B); }
    { const cuuint64_t d[2] = {512, 4096}, s[1] = {1024}; const cuuint32_t bx[2] = {64, 128};
      encode(fn, &m.wo, d_in[4], 2, d, s, bx, CU_TENSOR_MAP_SWIZZLE_128B, PROMO_W); }
    { const cuuint64_t d[2] = {1792, 512}, s[1] = {3584}; const cuuint32_t bx[2] = {16, 256};
      encode(fn, &m.w1, d_in[6], 2, d, s, bx, CU_TENSOR_MAP_SWIZZLE_32B); }
    { const cuuint64_t d[2] = {512, 1792}, s[1] = {1024}; const cuuint32_t bx[2] = {64, 112};
      encode(fn, &m.w2, d_in[7], 2, d, s, bx, CU_TENSOR_MAP_SWIZZLE_128B, PROMO_W); }

    cudaLaunchConfig_t cfg = {};
    cfg.gridDim = dim3(NCTA); cfg.blockDim = dim3(NTHREADS); cfg.dynamicSmemBytes = SMEM_BYTES;
    cfg.stream = cudaStreamPerThread;
    cudaLaunchAttribute at[2];
    at[0].id = cudaLaunchAttributeClusterDimension;
    at[0].val.clusterDim.x = CLUSTER; at[0].val.clusterDim.y = 1; at[0].val.clusterDim.z = 1;
    at[1].id = cudaLaunchAttributeClusterSchedulingPolicyPreference;
    at[1].val.clusterSchedulingPolicyPreference = cudaClusterSchedulingPolicyLoadBalancing;
    cfg.attrs = at; cfg.numAttrs = 2;
    cudaLaunchKernelEx(&cfg, fused_decode_kernel, m, (const char*)d_in[3], (__nv_bfloat16*)d_out, (const char*)d_in[1],
                       (const char*)d_in[2], (const char*)d_in[4], (const char*)d_in[6], (const char*)d_in[7]);
}
```

```cpp
#include <cuda_runtime.h>
#include <cuda_bf16.h>
#include <cuda.h>
#include <stdint.h>

namespace {

constexpr int NCTA = 128;
constexpr int CLUSTER = 16;
constexpr int NTHREADS = 288;
constexpr int CHUNK = 16384;
constexpr int NSLOT = 6;
constexpr int NCHUNK = 22;
constexpr int C_K = 3, C_V = 11, C_W2 = 19, C_WO = 20;
constexpr int DEPTH = 4;
constexpr int W2_AFTER = 16;
constexpr int WO_AFTER = 18;
constexpr int PF_BYTES = 8192;

constexpr int RED_PITCH = 36;
constexpr int OFF_U = NSLOT * CHUNK;
constexpr int OFF_X = OFF_U;
constexpr int OFF_RED = OFF_U;
constexpr int OFF_P = OFF_U;
constexpr int OFF_OB = OFF_U + 4096;
constexpr int OFF_RIN = OFF_U + 9216;
constexpr int OFF_Q = OFF_RIN + 4096;
constexpr int OFF_OST = OFF_Q;
constexpr int OFF_H = OFF_Q + 1024;
constexpr int OFF_ML = OFF_H + 2176;
constexpr int OFF_STAT = OFF_ML + 32;
constexpr int OFF_BAR = OFF_STAT + 336;
constexpr int SMEM_BYTES = OFF_BAR + 43 * 8;
static_assert(2 * (SMEM_BYTES + 1024) <= 233472, "two CTAs per SM");

struct Maps { CUtensorMap x, wq, k, v, w1, wo, w2; };

__device__ unsigned int g_epoch;
__device__ __align__(128) uint32_t g_o[2 * 8 * 32 * 64];
__device__ __align__(128) uint32_t g_h[8 * 896];

struct Watchdog {
    long long t0 = 0;
    __device__ __forceinline__ void tick() {
        const long long now = clock64();
        if (t0 == 0) t0 = now;
        else if (now - t0 > 4000000000ll) __trap();
    }
};

__device__ __forceinline__ uint32_t smem_u32(const void* p) { return (uint32_t)__cvta_generic_to_shared(p); }
__device__ __forceinline__ void mbar_init(uint32_t bar, uint32_t cnt) {
    asm volatile("mbarrier.init.shared::cta.b64 [%0], %1;" :: "r"(bar), "r"(cnt) : "memory");
}
__device__ __forceinline__ void mbar_expect(uint32_t bar, uint32_t bytes) {
    asm volatile("mbarrier.arrive.expect_tx.shared::cta.b64 _, [%0], %1;" :: "r"(bar), "r"(bytes) : "memory");
}
__device__ __forceinline__ void mbar_arrive(uint32_t bar) {
    asm volatile("mbarrier.arrive.shared::cta.b64 _, [%0];" :: "r"(bar) : "memory");
}
__device__ __forceinline__ bool mbar_try(uint32_t bar) {
    uint32_t done;
    asm volatile("{\n.reg .pred p;\nmbarrier.try_wait.parity.shared::cta.b64 p, [%1], 0;\nselp.u32 %0, 1, 0, p;\n}"
                 : "=r"(done) : "r"(bar) : "memory");
    return done;
}
__device__ __forceinline__ bool mbar_test(uint32_t bar) {
    uint32_t done;
    asm volatile("{\n.reg .pred p;\nmbarrier.test_wait.parity.shared::cta.b64 p, [%1], 0;\nselp.u32 %0, 1, 0, p;\n}"
                 : "=r"(done) : "r"(bar) : "memory");
    return done;
}
__device__ __forceinline__ void mbar_wait(uint32_t bar) {
    if (mbar_try(bar)) return;
    Watchdog wd;
    while (!mbar_try(bar)) wd.tick();
}
__device__ __forceinline__ uint32_t mapa(uint32_t addr, uint32_t rank) {
    uint32_t r; asm("mapa.shared::cluster.u32 %0, %1, %2;" : "=r"(r) : "r"(addr), "r"(rank)); return r;
}
__device__ __forceinline__ void st_async2(uint32_t dst, uint32_t a, uint32_t b, uint32_t bar) {
    asm volatile("st.async.weak.shared::cluster.mbarrier::complete_tx::bytes.v2.b32 [%0], {%1,%2}, [%3];"
                 :: "r"(dst), "r"(a), "r"(b), "r"(bar) : "memory");
}
__device__ __forceinline__ void st_async4(uint32_t dst, uint32_t a, uint32_t b, uint32_t c, uint32_t d, uint32_t bar) {
    asm volatile("st.async.weak.shared::cluster.mbarrier::complete_tx::bytes.v4.b32 [%0], {%1,%2,%3,%4}, [%5];"
                 :: "r"(dst), "r"(a), "r"(b), "r"(c), "r"(d), "r"(bar) : "memory");
}
__device__ __forceinline__ void tma2d(uint32_t dst, const CUtensorMap* m, int c0, int c1, uint32_t bar) {
    asm volatile("cp.async.bulk.tensor.2d.shared::cluster.global.mbarrier::complete_tx::bytes [%0], [%1, {%3, %4}], [%2];"
                 :: "r"(dst), "l"(m), "r"(bar), "r"(c0), "r"(c1) : "memory");
}
__device__ __forceinline__ void tma3d(uint32_t dst, const CUtensorMap* m, int c0, int c1, int c2, uint32_t bar) {
    asm volatile("cp.async.bulk.tensor.3d.shared::cluster.global.mbarrier::complete_tx::bytes [%0], [%1, {%3, %4, %5}], [%2];"
                 :: "r"(dst), "l"(m), "r"(bar), "r"(c0), "r"(c1), "r"(c2) : "memory");
}
__device__ __forceinline__ void l2_prefetch(const void* src, uint32_t bytes) {
    asm volatile("cp.async.bulk.prefetch.L2.global [%0], %1;" :: "l"(src), "r"(bytes) : "memory");
}
__device__ __forceinline__ void ldsm4(uint32_t (&r)[4], uint32_t addr) {
    asm volatile("ldmatrix.sync.aligned.m8n8.x4.shared.b16 {%0,%1,%2,%3}, [%4];"
                 : "=r"(r[0]), "=r"(r[1]), "=r"(r[2]), "=r"(r[3]) : "r"(addr) : "memory");
}
__device__ __forceinline__ void ldsm4t(uint32_t (&r)[4], uint32_t addr) {
    asm volatile("ldmatrix.sync.aligned.m8n8.x4.trans.shared.b16 {%0,%1,%2,%3}, [%4];"
                 : "=r"(r[0]), "=r"(r[1]), "=r"(r[2]), "=r"(r[3]) : "r"(addr) : "memory");
}
__device__ __forceinline__ void mma16816(float (&d)[4], const uint32_t (&a)[4], uint32_t b0, uint32_t b1) {
    asm volatile("mma.sync.aligned.m16n8k16.row.col.f32.bf16.bf16.f32 {%0,%1,%2,%3}, {%4,%5,%6,%7}, {%8,%9}, {%0,%1,%2,%3};"
                 : "+f"(d[0]), "+f"(d[1]), "+f"(d[2]), "+f"(d[3])
                 : "r"(a[0]), "r"(a[1]), "r"(a[2]), "r"(a[3]), "r"(b0), "r"(b1));
}
__device__ __forceinline__ uint32_t movtrans(uint32_t a) {
    uint32_t d;
    asm volatile("movmatrix.sync.aligned.m8n8.trans.b16 %0, %1;" : "=r"(d) : "r"(a));
    return d;
}
__device__ __forceinline__ uint32_t pack_bf16(float lo, float hi) {
    uint32_t d;
    asm("cvt.rn.bf16x2.f32 %0, %1, %2;" : "=r"(d) : "f"(hi), "f"(lo));
    return d;
}
__device__ __forceinline__ float bf16r(float x) { return __bfloat162float(__float2bfloat16_rn(x)); }
__device__ __forceinline__ float bf_lo(uint32_t u) { return __uint_as_float(u << 16); }
__device__ __forceinline__ float bf_hi(uint32_t u) { return __uint_as_float(u & 0xffff0000u); }
__device__ __forceinline__ uint32_t hadd2_bf16(uint32_t a, uint32_t b) {
    uint32_t d;
    asm("add.rn.bf16x2 %0, %1, %2;" : "=r"(d) : "r"(a), "r"(b));
    return d;
}
__device__ __forceinline__ uint32_t ld_rlx(const uint32_t* p) {
    uint32_t v; asm volatile("ld.relaxed.gpu.global.u32 %0, [%1];" : "=r"(v) : "l"(p) : "memory"); return v;
}
__device__ __forceinline__ void st_rlx(uint32_t* p, uint32_t v) {
    asm volatile("st.relaxed.gpu.global.u32 [%0], %1;" :: "l"(p), "r"(v) : "memory");
}
__device__ __forceinline__ uint4 ld_rlx_2x64(const void* p) {
    unsigned long long a, b;
    asm volatile("ld.relaxed.gpu.global.v2.b64 {%0,%1}, [%2];" : "=l"(a), "=l"(b) : "l"(p) : "memory");
    return make_uint4((uint32_t)a, (uint32_t)(a >> 32), (uint32_t)b, (uint32_t)(b >> 32));
}
__device__ __forceinline__ void st_rlx_2x64(void* p, const uint4& v) {
    asm volatile("st.relaxed.gpu.global.v2.b64 [%0], {%1,%2};" :: "l"(p),
                 "l"(((unsigned long long)v.y << 32) | v.x), "l"(((unsigned long long)v.w << 32) | v.z) : "memory");
}
__device__ __forceinline__ void st_rlx_64(void* p, uint32_t lo, uint32_t hi) {
    asm volatile("st.relaxed.gpu.global.b64 [%0], %1;" :: "l"(p), "l"(((unsigned long long)hi << 32) | lo) : "memory");
}
__device__ __forceinline__ bool tagged(const uint4& v, uint32_t tag) { return (((v.x ^ tag) | (v.z ^ tag)) & 1u) == 0u; }
__device__ __forceinline__ void sts128(uint32_t a, uint32_t x, uint32_t y, uint32_t z, uint32_t w) {
    asm volatile("st.shared.v4.b32 [%0], {%1,%2,%3,%4};" :: "r"(a), "r"(x), "r"(y), "r"(z), "r"(w) : "memory");
}
template <typename T> __device__ __forceinline__ void pin64(T*& p) { asm volatile("" : "+l"(p)); }
__device__ __forceinline__ void pin32(uint32_t& v) { asm volatile("" : "+r"(v)); }
__device__ __forceinline__ void cbar() { asm volatile("bar.sync 1, 256;" ::: "memory"); }
__device__ __forceinline__ float ex2(float x) { float y; asm("ex2.approx.ftz.f32 %0, %1;" : "=f"(y) : "f"(x)); return y; }

__global__ void __launch_bounds__(NTHREADS, 2)
fused_decode_kernel(const __grid_constant__ Maps maps, const char* __restrict__ wq_raw, __nv_bfloat16* __restrict__ out)
{
    extern __shared__ __align__(1024) char smp[];
    const uint32_t sm = smem_u32(smp);
    const int tid = threadIdx.x, warp = tid >> 5, lane = tid & 31;
    const int cta = blockIdx.x, g = cta >> 4, c = cta & 15, b = c >> 1, half = c & 1;
    const bool ffn = g < 7;
    const uint32_t bar_full = sm + OFF_BAR, bar_empty = bar_full + NCHUNK * 8;
    const uint32_t bar_q = bar_empty + 16 * 8, bar_ml = bar_q + 8, bar_r = bar_q + 16, bar_x = bar_q + 24, bar_ob = bar_q + 32;

    if (warp == 8) {
        if (lane == 0) {
            mbar_init(bar_x, 1); mbar_init(bar_full, 1); mbar_init(bar_full + 8, 1);
            asm volatile("fence.proxy.async.shared::cta;" ::: "memory");
            mbar_expect(bar_full, CHUNK); tma2d(sm, &maps.wq, cta * 32, 0, bar_full);
            mbar_expect(bar_x, 8192); tma3d(sm + OFF_X, &maps.x, 0, 0, 0, bar_x);
            mbar_expect(bar_full + 8, CHUNK); tma2d(sm + CHUNK, &maps.wq, cta * 32, 256, bar_full + 8);
            if (sm & 1023u) __trap();
            #pragma unroll
            for (int s = 2; s < NCHUNK; s++) mbar_init(bar_full + s * 8, 1);
            #pragma unroll
            for (int s = 0; s < 16; s++) mbar_init(bar_empty + s * 8, s < 2 ? 4 : (s >= C_K && s < C_V) ? 1 : 8);
            mbar_init(bar_q, 1); mbar_init(bar_ml, 1); mbar_init(bar_r, 1); mbar_init(bar_ob, 8);
            mbar_expect(bar_q, 1024); mbar_expect(bar_ml, 32); mbar_expect(bar_r, 4096);
            asm volatile("fence.mbarrier_init.release.cluster;" ::: "memory");
            asm volatile("fence.proxy.async.shared::cta;" ::: "memory");
        }
        __syncwarp();
        asm volatile("barrier.cluster.arrive.relaxed.aligned;" ::: "memory");
        asm volatile("bar.arrive 2, %0;" :: "n"(NTHREADS) : "memory");
        if (lane == 0) {
            if (ffn) {
                mbar_expect(bar_full + 16, CHUNK);
                tma2d(sm + 2 * CHUNK, &maps.w1, cta * 16, 0, bar_full + 16);
                tma2d(sm + 2 * CHUNK + 8192, &maps.w1, cta * 16, 256, bar_full + 16);
            } else mbar_arrive(bar_full + 16);
            const int row0 = (b * 8 + g) * 4096 + 3072 + half * 512;
            uint32_t dst = sm + C_K * CHUNK;
            #pragma unroll 1
            for (int ch = C_K; ch < NCHUNK; ch++) {
                if (ch >= DEPTH) mbar_wait(bar_full + (ch < C_W2 ? ch - DEPTH : ch == C_W2 ? W2_AFTER : WO_AFTER) * 8);
                if (ch >= NSLOT) mbar_wait(bar_empty + (ch - NSLOT) * 8);
                const uint32_t bar = bar_full + ch * 8;
                if (ch < C_W2) {
                    mbar_expect(bar, CHUNK);
                    tma3d(dst, ch < C_V ? &maps.k : &maps.v, 0, row0 + ((ch - C_K) & 7) * 64, 0, bar);
                } else {
                    mbar_expect(bar, ch == C_W2 ? 14336 : CHUNK);
                    tma2d(dst, ch == C_W2 ? &maps.w2 : &maps.wo, g * 64,
                          ch == C_W2 ? c * 112 : c * 256 + (ch - C_WO) * 128, bar);
                }
                dst = (dst == sm + (NSLOT - 1) * CHUNK) ? sm : dst + CHUNK;
            }
        }
        __syncwarp();
        asm volatile("barrier.cluster.wait.aligned;" ::: "memory");
        return;
    }

    if (tid == 0) l2_prefetch(wq_raw + (size_t)cta * 32768, PF_BYTES);
    asm volatile("barrier.cluster.arrive.relaxed.aligned;" ::: "memory");
    const int gl = lane >> 2, t = lane & 3;
    float* lnst = reinterpret_cast<float*>(smp + OFF_STAT + 256);
    volatile uint32_t* epoch_s = reinterpret_cast<volatile uint32_t*>(smp + OFF_STAT + 320);
    const int ru = lane & 7, rp = lane >> 3;
    const int ob = 2 * (ru & 3) + (rp & 1);
    const int ocol = g * 64 + (c >> 2) * 16 + 2 * (c & 3) + (ru >> 2) + 8 * (rp >> 1);
    uint32_t epoch_r = 0;
    if (tid == 64) epoch_r = ld_rlx(&g_epoch);
    asm volatile("bar.sync 2, %0;" :: "n"(NTHREADS) : "memory");
    if (tid == 64) *epoch_s = epoch_r;
    mbar_wait(bar_x);
    uint32_t xf[8];
    #pragma unroll
    for (int j = 0; j < 8; j++)
        xf[j] = *reinterpret_cast<const uint32_t*>(smp + OFF_X + warp * 1024 + gl * 128 + ((j ^ gl) << 4) + t * 4);
    const float resid = __bfloat162float(*reinterpret_cast<const __nv_bfloat16*>(
        smp + OFF_X + g * 1024 + ob * 128 + ((((ocol >> 3) & 7) ^ ob) << 4) + (ocol & 7) * 2));
    {
        const char* xr = smp + OFF_X + (lane >> 3) * 1024 + warp * 128 + (lane & 7) * 16;
        const uint4 xa = *reinterpret_cast<const uint4*>(xr), xb = *reinterpret_cast<const uint4*>(xr + 4096);
        const float sh = bf_lo(*reinterpret_cast<const uint32_t*>(smp + OFF_X + warp * 128));
        const uint32_t w[8] = {xa.x, xa.y, xa.z, xa.w, xb.x, xb.y, xb.z, xb.w};
        float s4[4] = {}, q4[4] = {};
        #pragma unroll
        for (int j = 0; j < 8; j++) {
            const float lo = bf_lo(w[j]) - sh, hi = bf_hi(w[j]) - sh;
            s4[j & 3] += lo + hi;
            q4[j & 3] = fmaf(lo, lo, fmaf(hi, hi, q4[j & 3]));
        }
        float s = (s4[0] + s4[1]) + (s4[2] + s4[3]), q2 = (q4[0] + q4[1]) + (q4[2] + q4[3]);
        #pragma unroll
        for (int o = 16; o > 0; o >>= 1) {
            s += __shfl_xor_sync(0xffffffffu, s, o);
            q2 += __shfl_xor_sync(0xffffffffu, q2, o);
        }
        const float ms = s * (1.f / 512.f), mean = sh + ms;
        q2 = fmaxf(fmaf(-ms, s, q2), 0.f);
        const float den = bf16r(__fsqrt_rn(bf16r(bf16r(q2 * (1.f / 512.f)) + 1e-5f)));
        if (lane == 0) *reinterpret_cast<float2*>(lnst + warp * 2) = make_float2(bf16r(mean), __frcp_rn(den));
    }
    cbar();
    {
        const float2 st = *reinterpret_cast<const float2*>(lnst + gl * 2);
        #pragma unroll
        for (int j = 0; j < 8; j++)
            xf[j] = pack_bf16(bf16r(bf_lo(xf[j]) - st.x) * st.y, bf16r(bf_hi(xf[j]) - st.x) * st.y);
    }
    const uint32_t tag = (*epoch_s + 1u) & 1u;

    float* red = reinterpret_cast<float*>(smp + OFF_RED);
    const int mj = lane >> 3, mr = lane & 7;
    float* r0 = red + (warp * 8 + 2 * t) * RED_PITCH + gl;
    {
        float aq[2][4] = {};
        mbar_wait(bar_full + (warp >> 2) * 8);
        const uint32_t wqs = sm + (warp >> 2) * CHUNK;
        #pragma unroll
        for (int s = 0; s < 4; s++) {
            const int row = (warp & 3) * 64 + s * 16 + (mj >> 1) * 8 + mr;
            #pragma unroll
            for (int j = 0; j < 2; j++) {
                uint32_t a[4];
                ldsm4t(a, wqs + row * 64 + (((2 * j + (mj & 1)) ^ ((row >> 1) & 3)) << 4));
                mma16816(aq[j], a, xf[2 * s], xf[2 * s + 1]);
            }
        }
        __syncwarp();
        if (lane == 0) mbar_arrive(bar_empty + (warp >> 2) * 8);
        #pragma unroll
        for (int j = 0; j < 2; j++) {
            r0[j * 16] = aq[j][0]; r0[RED_PITCH + j * 16] = aq[j][1];
            r0[j * 16 + 8] = aq[j][2]; r0[RED_PITCH + j * 16 + 8] = aq[j][3];
        }
    }
    cbar();
    asm volatile("barrier.cluster.wait.aligned;" ::: "memory");
    if (warp < 4) {
        const int bb = tid >> 4, wd = tid & 15;
        const int col = (wd >> 3) * 16 + ((wd >> 1) & 3) * 2 + (wd & 1) * 8;
        float s0 = 0.f, s1 = 0.f;
        #pragma unroll
        for (int w = 0; w < 8; w++) {
            const float2 f = *reinterpret_cast<const float2*>(red + (w * 8 + bb) * RED_PITCH + col);
            s0 += f.x; s1 += f.y;
        }
        const uint32_t u = pack_bf16(s0, s1);
        const int q0 = (lane & 16) + (lane & 3) * 4;
        const uint32_t u0 = __shfl_sync(0xffffffffu, u, q0), u1 = __shfl_sync(0xffffffffu, u, q0 + 1);
        const uint32_t u2 = __shfl_sync(0xffffffffu, u, q0 + 2), u3 = __shfl_sync(0xffffffffu, u, q0 + 3);
        if (wd < 8) {
            const uint32_t rank = 2 * bb + (wd >> 2);
            st_async4(mapa(sm + OFF_Q + c * 64 + (wd & 3) * 16, rank), u0, u1, u2, u3, mapa(bar_q, rank));
        }
    }
    if (ffn) {
        float ah[4] = {};
        mbar_wait(bar_full + 2 * 8);
        const uint32_t w1s = sm + 2 * CHUNK;
        #pragma unroll
        for (int s = 0; s < 4; s++) {
            const int row = warp * 64 + s * 16 + (mj >> 1) * 8 + mr;
            uint32_t a[4];
            ldsm4t(a, w1s + row * 32 + (((mj & 1) ^ ((row >> 2) & 1)) << 4));
            mma16816(ah, a, xf[2 * s], xf[2 * s + 1]);
        }
        __syncwarp();
        if (lane == 0) mbar_arrive(bar_empty + 2 * 8);
        cbar();
        r0[0] = ah[0]; r0[RED_PITCH] = ah[1]; r0[8] = ah[2]; r0[RED_PITCH + 8] = ah[3];
        cbar();
        if (warp >= 6) {
            const int bb = (tid & 63) >> 3, wd = tid & 7;
            float s0 = 0.f, s1 = 0.f;
            #pragma unroll
            for (int w = 0; w < 8; w++) {
                const float2 f = *reinterpret_cast<const float2*>(red + (w * 8 + bb) * RED_PITCH + 2 * wd);
                s0 += f.x; s1 += f.y;
            }
            s0 = bf16r(s0); s1 = bf16r(s1);
            s0 = __fdividef(s0, 1.f + __expf(-s0)); s1 = __fdividef(s1, 1.f + __expf(-s1));
            const uint32_t u = pack_bf16(s0, s1);
            const uint32_t un = __shfl_down_sync(0xffffffffu, u, 1);
            if (!(wd & 1)) st_rlx_64(g_h + bb * 896 + cta * 8 + wd, (u & ~1u) | tag, un);
        }
    } else {
        __syncwarp();
        if (lane == 0) mbar_arrive(bar_empty + 2 * 8);
    }

    float sc[4][4];
    {
        mbar_wait(bar_q);
        uint32_t qb[8][2];
        #pragma unroll
        for (int s = 0; s < 8; s++) {
            const uint2 v = *reinterpret_cast<const uint2*>(smp + OFF_Q + (((gl & 3) * 8 + s) * 4 + t) * 8);
            qb[s][0] = v.x; qb[s][1] = v.y;
        }
        mbar_wait(bar_full + (C_K + warp) * 8);
        const uint32_t ks = sm + ((C_K + warp) % NSLOT) * CHUNK;
        #pragma unroll
        for (int i = 0; i < 4; i++) { sc[i][0] = sc[i][1] = sc[i][2] = sc[i][3] = 0.f; }
        #pragma unroll
        for (int s = 0; s < 8; s++) {
            const int ch = 2 * s + (mj >> 1);
            #pragma unroll
            for (int i = 0; i < 4; i++) {
                const int row = i * 16 + (mj & 1) * 8 + mr;
                uint32_t a[4];
                ldsm4(a, ks + (ch >> 3) * 8192 + row * 128 + (((ch & 7) ^ mr) << 4));
                mma16816(sc[i], a, qb[s][0], qb[s][1]);
            }
        }
        __syncwarp();
        if (lane == 0) mbar_arrive(bar_empty + (C_K + warp) * 8);
    }
    float* wmax = reinterpret_cast<float*>(smp + OFF_STAT);
    float* wsum = wmax + 32;
    float m0, m1;
    constexpr float L2E = 1.4426950408889634f;
    {
        m0 = -INFINITY; m1 = -INFINITY;
        #pragma unroll
        for (int i = 0; i < 4; i++) {
            #pragma unroll
            for (int k = 0; k < 4; k++) sc[i][k] = bf16r(bf16r(sc[i][k]) * 0.08838834764831845f);
            m0 = fmaxf(m0, fmaxf(sc[i][0], sc[i][2]));
            m1 = fmaxf(m1, fmaxf(sc[i][1], sc[i][3]));
        }
        #pragma unroll
        for (int o = 4; o < 32; o <<= 1) {
            m0 = fmaxf(m0, __shfl_xor_sync(0xffffffffu, m0, o));
            m1 = fmaxf(m1, __shfl_xor_sync(0xffffffffu, m1, o));
        }
        if (lane < 2) *reinterpret_cast<float2*>(wmax + warp * 4 + 2 * lane) = make_float2(m0, m1);
        cbar();
        #pragma unroll
        for (int w = 0; w < 8; w++) {
            const float2 f = *reinterpret_cast<const float2*>(wmax + w * 4 + 2 * (t & 1));
            m0 = fmaxf(m0, f.x); m1 = fmaxf(m1, f.y);
        }
        float l0 = 0.f, l1 = 0.f;
        uint32_t pw[4][2];
        #pragma unroll
        for (int i = 0; i < 4; i++) {
            const float p0 = ex2((sc[i][0] - m0) * L2E), p1 = ex2((sc[i][1] - m1) * L2E);
            const float p2 = ex2((sc[i][2] - m0) * L2E), p3 = ex2((sc[i][3] - m1) * L2E);
            l0 += p0 + p2; l1 += p1 + p3;
            pw[i][0] = movtrans(pack_bf16(p0, p1));
            pw[i][1] = movtrans(pack_bf16(p2, p3));
        }
        if (lane < 16) {
            uint4* pd = reinterpret_cast<uint4*>(smp + OFF_P) + (warp * 2) * 16 + lane;
            pd[0] = make_uint4(pw[0][0], pw[0][1], pw[1][0], pw[1][1]);
            pd[16] = make_uint4(pw[2][0], pw[2][1], pw[3][0], pw[3][1]);
        }
        #pragma unroll
        for (int o = 4; o < 32; o <<= 1) {
            l0 += __shfl_xor_sync(0xffffffffu, l0, o);
            l1 += __shfl_xor_sync(0xffffffffu, l1, o);
        }
        if (lane < 2) *reinterpret_cast<float2*>(wsum + warp * 4 + 2 * lane) = make_float2(l0, l1);
    }
    cbar();
    float l0 = 0.f, l1 = 0.f;
    #pragma unroll
    for (int w = 0; w < 8; w++) {
        const float2 f = *reinterpret_cast<const float2*>(wsum + w * 4 + 2 * (t & 1));
        l0 += f.x; l1 += f.y;
    }
    if (tid < 2) {
        const uint32_t dst = mapa(sm + OFF_ML + tid * 8, c ^ 1), bar = mapa(bar_ml, c ^ 1);
        st_async2(dst, __float_as_uint(m0), __float_as_uint(m1), bar);
        st_async2(dst + 16, __float_as_uint(l0), __float_as_uint(l1), bar);
    }

    const uint32_t* op = g_o + (((tid >> 4) & 7) * 32 + 2 * c + (tid >> 7)) * 64 + (tid & 15) * 4;
    uint32_t* opub = g_o + ((half * 8 + b) * 32 + g * 4) * 64 + (tid & 63) * 4;
    __nv_bfloat16* outp = out + ob * 512 + ocol;
    uint32_t s_ost = sm + OFF_OST + gl * 256 + (t * 4 + ((warp >> 1) ^ (t & 2))) * 16 + (warp & 1) * 8;
    uint32_t s_rdst = mapa(sm + OFF_RIN + (c * 2 + (warp >> 2)) * 128 + ru * 16, (warp & 3) * 4 + rp);
    uint32_t s_rbar = mapa(bar_r, (warp & 3) * 4 + rp);
    uint32_t s_obw = sm + OFF_OB + (tid >> 4) * 320 + (((tid & 15) ^ ((tid >> 4) & 1)) << 4);
    uint32_t s_obr = sm + OFF_OB + gl * 320 + t * 64 + ((((warp >> 2) * 2) ^ (t & 2) ^ (gl & 1)) << 4);
    const int hb = min(tid / 14, 7), hpc = tid - (tid / 14) * 14;
    const uint32_t* hp = g_h + hb * 896 + c * 56 + hpc * 4;
    uint32_t s_h = sm + OFF_H + hb * 272 + hpc * 16;
    pin64(op); pin64(opub); pin64(outp); pin64(hp);
    pin32(s_ost); pin32(s_rdst); pin32(s_rbar); pin32(s_obw); pin32(s_obr); pin32(s_h);
    uint4 hv = make_uint4(tag, 0u, tag, 0u);
    if (tid < 112) hv = ld_rlx_2x64(hp);
    if (tid < 64) st_rlx_2x64(opub, make_uint4(tag ^ 1u, 0u, tag ^ 1u, 0u));

    float f0 = 0.f, f1 = 0.f;
    float oc[4][4] = {};
    {
        const int ach = 2 * warp + (mj & 1);
        const uint32_t voff = (ach >> 3) * 8192 + ((mj >> 1) * 8 + mr) * 128 + (((ach & 7) ^ mr) << 4);
        const uint4* pfp = reinterpret_cast<const uint4*>(smp + OFF_P) + (lane & 15);
        uint32_t vs = sm + (C_V % NSLOT) * CHUNK;
        #pragma unroll 1
        for (int j = 0; j < 8; j++) {
            const uint4 pa = pfp[j * 32], pb = pfp[j * 32 + 16];
            if (j == 6) {
                if (!tagged(hv, tag)) {
                    Watchdog wd;
                    do { hv = ld_rlx_2x64(hp); wd.tick(); } while (!tagged(hv, tag));
                }
                if (tid < 112) sts128(s_h, hv.x, hv.y, hv.z, hv.w);
                __syncwarp();
                mbar_wait(bar_ml);
                const float* pm = reinterpret_cast<const float*>(smp + OFF_ML) + (t & 1) * 2;
                const float mo0 = pm[0], mo1 = pm[1];
                const float mt0 = fmaxf(m0, mo0), mt1 = fmaxf(m1, mo1);
                const float e0 = ex2((m0 - mt0) * L2E), e1 = ex2((m1 - mt1) * L2E);
                f0 = __fdividef(e0, l0 * e0 + pm[4] * ex2((mo0 - mt0) * L2E));
                f1 = __fdividef(e1, l1 * e1 + pm[5] * ex2((mo1 - mt1) * L2E));
            }
            mbar_wait(bar_full + (C_V + j) * 8);
            uint32_t a[4][4];
            #pragma unroll
            for (int s = 0; s < 4; s++) ldsm4t(a[s], vs + voff + s * 2048);
            mma16816(oc[0], a[0], pa.x, pa.y);
            mma16816(oc[1], a[1], pa.z, pa.w);
            mma16816(oc[2], a[2], pb.x, pb.y);
            mma16816(oc[3], a[3], pb.z, pb.w);
            __syncwarp();
            if (j < 5 && lane == 0) mbar_arrive(bar_empty + (C_V + j) * 8);
            vs = (vs == sm + (NSLOT - 1) * CHUNK) ? sm : vs + CHUNK;
        }
    }
    {
        const float o0 = (oc[0][0] + oc[1][0]) + (oc[2][0] + oc[3][0]);
        const float o1 = (oc[0][1] + oc[1][1]) + (oc[2][1] + oc[3][1]);
        const float o2 = (oc[0][2] + oc[1][2]) + (oc[2][2] + oc[3][2]);
        const float o3 = (oc[0][3] + oc[1][3]) + (oc[2][3] + oc[3][3]);
        const uint32_t u0 = movtrans(pack_bf16(o0 * f0, o1 * f1));
        const uint32_t u1 = movtrans(pack_bf16(o2 * f0, o3 * f1));
        if (lane < 16)
            asm volatile("st.shared.v2.b32 [%0], {%1,%2};" :: "r"(s_ost), "r"((u0 & ~1u) | tag), "r"(u1) : "memory");
        cbar();
        if (tid < 64) st_rlx_2x64(opub, *reinterpret_cast<const uint4*>(smp + OFF_OST + tid * 16));
    }

    {
        const int mt = warp & 3, kh = warp >> 2;
        const uint32_t aoff = kh * 8192 + ((mj >> 1) * 8 + mr) * 128 + (((2 * mt + (mj & 1)) ^ mr) << 4);
        float ac[4][4] = {};
        mbar_wait(bar_full + C_W2 * 8);
        {
            const uint32_t* hs = reinterpret_cast<const uint32_t*>(smp + OFF_H) + gl * 68 + kh * 32 + t;
            #pragma unroll
            for (int s = 0; s < 4; s++) {
                if (s < 3 || kh == 0) {
                    uint32_t a[4];
                    ldsm4t(a, sm + (C_W2 % NSLOT) * CHUNK + aoff + s * 2048);
                    mma16816(ac[s], a, hs[s * 8], hs[s * 8 + 4]);
                }
            }
        }
        uint32_t wa[8][4];
        bool have0 = false, have1 = false;
        auto wo_part = [&](int i) {
            #pragma unroll
            for (int s = 0; s < 4; s++) ldsm4t(wa[i * 4 + s], sm + (C_WO % NSLOT + i) * CHUNK + aoff + s * 2048);
        };
        uint4 oa = make_uint4(tag ^ 1u, 0u, 0u, 0u), obv = oa;
        Watchdog wd;
        for (;;) {
            const bool na = !tagged(oa, tag), nb = !tagged(obv, tag);
            if (!__any_sync(0xffffffffu, na || nb)) break;
            if (na) oa = ld_rlx_2x64(op);
            if (nb) obv = ld_rlx_2x64(op + 16384);
            if (!have0 && mbar_test(bar_full + C_WO * 8)) { have0 = true; wo_part(0); }
            if (!have1 && mbar_test(bar_full + (C_WO + 1) * 8)) { have1 = true; wo_part(1); }
            wd.tick();
        }
        sts128(s_obw, hadd2_bf16(oa.x, obv.x), hadd2_bf16(oa.y, obv.y), hadd2_bf16(oa.z, obv.z), hadd2_bf16(oa.w, obv.w));
        __syncwarp();
        if (lane == 0) mbar_arrive(bar_ob);
        if (!have0 && mbar_test(bar_full + C_WO * 8)) { have0 = true; wo_part(0); }
        if (!have1 && mbar_test(bar_full + (C_WO + 1) * 8)) { have1 = true; wo_part(1); }
        mbar_wait(bar_ob);
        uint4 of[4];
        #pragma unroll
        for (int i = 0; i < 4; i++)
            asm volatile("ld.shared.v4.b32 {%0,%1,%2,%3}, [%4];" : "=r"(of[i].x), "=r"(of[i].y), "=r"(of[i].z), "=r"(of[i].w)
                         : "r"((s_obr ^ ((i & 1) << 4)) + (i >> 1) * 2560) : "memory");
        if (!have0) { mbar_wait(bar_full + C_WO * 8); wo_part(0); }
        mma16816(ac[0], wa[0], of[0].x, of[0].y);
        mma16816(ac[1], wa[1], of[0].z, of[0].w);
        mma16816(ac[2], wa[2], of[1].x, of[1].y);
        mma16816(ac[3], wa[3], of[1].z, of[1].w);
        if (!have1) { mbar_wait(bar_full + (C_WO + 1) * 8); wo_part(1); }
        mma16816(ac[0], wa[4], of[2].x, of[2].y);
        mma16816(ac[1], wa[5], of[2].z, of[2].w);
        mma16816(ac[2], wa[6], of[3].x, of[3].y);
        mma16816(ac[3], wa[7], of[3].z, of[3].w);
        st_async4(s_rdst,
                  __float_as_uint((ac[0][0] + ac[1][0]) + (ac[2][0] + ac[3][0])),
                  __float_as_uint((ac[0][1] + ac[1][1]) + (ac[2][1] + ac[3][1])),
                  __float_as_uint((ac[0][2] + ac[1][2]) + (ac[2][2] + ac[3][2])),
                  __float_as_uint((ac[0][3] + ac[1][3]) + (ac[2][3] + ac[3][3])), s_rbar);
    }

    if (warp == 0) {
        mbar_wait(bar_r);
        float4 v[8];
        #pragma unroll
        for (int i = 0; i < 8; i++) v[i] = *reinterpret_cast<const float4*>(smp + OFF_RIN + (i * 4 + rp) * 128 + ru * 16);
        const float s0 = ((v[0].x + v[1].x) + (v[2].x + v[3].x)) + ((v[4].x + v[5].x) + (v[6].x + v[7].x));
        const float s1 = ((v[0].y + v[1].y) + (v[2].y + v[3].y)) + ((v[4].y + v[5].y) + (v[6].y + v[7].y));
        const float s2 = ((v[0].z + v[1].z) + (v[2].z + v[3].z)) + ((v[4].z + v[5].z) + (v[6].z + v[7].z));
        const float s3 = ((v[0].w + v[1].w) + (v[2].w + v[3].w)) + ((v[4].w + v[5].w) + (v[6].w + v[7].w));
        float a = (rp & 1) ? s1 : s0, bq = (rp & 1) ? s3 : s2;
        a += __shfl_xor_sync(0xffffffffu, (rp & 1) ? s0 : s1, 8);
        bq += __shfl_xor_sync(0xffffffffu, (rp & 1) ? s2 : s3, 8);
        float r = (rp & 2) ? bq : a;
        r += __shfl_xor_sync(0xffffffffu, (rp & 2) ? a : bq, 16);
        *outp = __float2bfloat16_rn(r + resid);
        if (cta == 0 && lane == 0) st_rlx(&g_epoch, *epoch_s + 1u);
    }
}

typedef CUresult (*EncodeFn)(CUtensorMap*, CUtensorMapDataType, cuuint32_t, void*, const cuuint64_t*, const cuuint64_t*,
                             const cuuint32_t*, const cuuint32_t*, CUtensorMapInterleave, CUtensorMapSwizzle,
                             CUtensorMapL2promotion, CUtensorMapFloatOOBfill);

void encode(EncodeFn fn, CUtensorMap* m, const void* p, int rank, const cuuint64_t* dims, const cuuint64_t* strides,
            const cuuint32_t* box, CUtensorMapSwizzle sw) {
    const cuuint32_t es[3] = {1, 1, 1};
    fn(m, CU_TENSOR_MAP_DATA_TYPE_BFLOAT16, rank, const_cast<void*>(p), dims, strides, box, es,
       CU_TENSOR_MAP_INTERLEAVE_NONE, sw, CU_TENSOR_MAP_L2_PROMOTION_L2_256B, CU_TENSOR_MAP_FLOAT_OOB_FILL_NONE);
}

}

extern "C" void kernel_launch(void* const* d_in, const int* in_sizes, int n_in, void* d_out, int out_size) {
    (void)in_sizes; (void)n_in; (void)out_size;
    static EncodeFn fn = nullptr;
    if (!fn) {
        cudaDriverEntryPointQueryResult qr;
        cudaGetDriverEntryPoint("cuTensorMapEncodeTiled", (void**)&fn, cudaEnableDefault, &qr);
        cudaFuncSetAttribute(fused_decode_kernel, cudaFuncAttributeMaxDynamicSharedMemorySize, SMEM_BYTES);
        cudaFuncSetAttribute(fused_decode_kernel, cudaFuncAttributeNonPortableClusterSizeAllowed, 1);
    }
    Maps m;
    {
        const cuuint64_t d[3] = {64, 64ull * 4096, 2}, s[2] = {256, 128};
        const cuuint32_t bx[3] = {64, 64, 2};
        encode(fn, &m.k, d_in[1], 3, d, s, bx, CU_TENSOR_MAP_SWIZZLE_128B);
        encode(fn, &m.v, d_in[2], 3, d, s, bx, CU_TENSOR_MAP_SWIZZLE_128B);
    }
    { const cuuint64_t d[3] = {64, 8, 8}, s[2] = {1024, 128}; const cuuint32_t bx[3] = {64, 8, 8};
      encode(fn, &m.x, d_in[0], 3, d, s, bx, CU_TENSOR_MAP_SWIZZLE_128B); }
    { const cuuint64_t d[2] = {4096, 512}, s[1] = {8192}; const cuuint32_t bx[2] = {32, 256};
      encode(fn, &m.wq, d_in[3], 2, d, s, bx, CU_TENSOR_MAP_SWIZZLE_64B); }
    { const cuuint64_t d[2] = {512, 4096}, s[1] = {1024}; const cuuint32_t bx[2] = {64, 128};
      encode(fn, &m.wo, d_in[4], 2, d, s, bx, CU_TENSOR_MAP_SWIZZLE_128B); }
    { const cuuint64_t d[2] = {1792, 512}, s[1] = {3584}; const cuuint32_t bx[2] = {16, 256};
      encode(fn, &m.w1, d_in[6], 2, d, s, bx, CU_TENSOR_MAP_SWIZZLE_32B); }
    { const cuuint64_t d[2] = {512, 1792}, s[1] = {1024}; const cuuint32_t bx[2] = {64, 112};
      encode(fn, &m.w2, d_in[7], 2, d, s, bx, CU_TENSOR_MAP_SWIZZLE_128B); }

    cudaLaunchConfig_t cfg = {};
    cfg.gridDim = dim3(NCTA); cfg.blockDim = dim3(NTHREADS); cfg.dynamicSmemBytes = SMEM_BYTES;
    cfg.stream = cudaStreamPerThread;
    cudaLaunchAttribute at[2];
    at[0].id = cudaLaunchAttributeClusterDimension;
    at[0].val.clusterDim.x = CLUSTER; at[0].val.clusterDim.y = 1; at[0].val.clusterDim.z = 1;
    at[1].id = cudaLaunchAttributeClusterSchedulingPolicyPreference;
    at[1].val.clusterSchedulingPolicyPreference = cudaClusterSchedulingPolicyLoadBalancing;
    cfg.attrs = at; cfg.numAttrs = 2;
    cudaLaunchKernelEx(&cfg, fused_decode_kernel, m, (const char*)d_in[3], (__nv_bfloat16*)d_out);
}
```

```cpp
#include <cuda_runtime.h>
#include <cuda_bf16.h>
#include <cuda.h>
#include <stdint.h>

namespace {

constexpr int NCTA = 128;
constexpr int CLUSTER = 16;
constexpr int NTHREADS = 288;
constexpr int CHUNK = 16384;
constexpr int NSLOT = 6;
constexpr int NCHUNK = 22;
constexpr int C_K = 3, C_V = 11, C_W2 = 19, C_WO = 20;
constexpr int DEPTH = 4;
constexpr int W2_AFTER = 16;
constexpr int WO_AFTER = 18;
constexpr int PF_BYTES = 8192;

constexpr int RED_PITCH = 36;
constexpr int OFF_U = NSLOT * CHUNK;
constexpr int OFF_X = OFF_U;
constexpr int OFF_RED = OFF_U;
constexpr int OFF_P = OFF_U;
constexpr int OFF_OB = OFF_U + 4096;
constexpr int OFF_RIN = OFF_U + 9216;
constexpr int OFF_Q = OFF_RIN + 4096;
constexpr int OFF_OST = OFF_Q;
constexpr int OFF_H = OFF_Q + 1024;
constexpr int OFF_ML = OFF_H + 2176;
constexpr int OFF_STAT = OFF_ML + 32;
constexpr int OFF_BAR = OFF_STAT + 336;
constexpr int SMEM_BYTES = OFF_BAR + 42 * 8;
static_assert(2 * (SMEM_BYTES + 1024) <= 233472, "two CTAs per SM");

struct Maps { CUtensorMap x, wq, k, v, w1, wo, w2; };

__device__ unsigned int g_epoch;
__device__ __align__(128) uint32_t g_o[2 * 8 * 32 * 64];
__device__ __align__(128) uint32_t g_h[8 * 896];

struct Watchdog {
    long long t0 = 0;
    __device__ __forceinline__ void tick() {
        const long long now = clock64();
        if (t0 == 0) t0 = now;
        else if (now - t0 > 4000000000ll) __trap();
    }
};

__device__ __forceinline__ uint32_t smem_u32(const void* p) { return (uint32_t)__cvta_generic_to_shared(p); }
__device__ __forceinline__ void mbar_init(uint32_t bar, uint32_t cnt) {
    asm volatile("mbarrier.init.shared::cta.b64 [%0], %1;" :: "r"(bar), "r"(cnt) : "memory");
}
__device__ __forceinline__ void mbar_expect(uint32_t bar, uint32_t bytes) {
    asm volatile("mbarrier.arrive.expect_tx.shared::cta.b64 _, [%0], %1;" :: "r"(bar), "r"(bytes) : "memory");
}
__device__ __forceinline__ void mbar_arrive(uint32_t bar) {
    asm volatile("mbarrier.arrive.shared::cta.b64 _, [%0];" :: "r"(bar) : "memory");
}
__device__ __forceinline__ bool mbar_try(uint32_t bar) {
    uint32_t done;
    asm volatile("{\n.reg .pred p;\nmbarrier.try_wait.parity.shared::cta.b64 p, [%1], 0;\nselp.u32 %0, 1, 0, p;\n}"
                 : "=r"(done) : "r"(bar) : "memory");
    return done;
}
__device__ __forceinline__ bool mbar_test(uint32_t bar) {
    uint32_t done;
    asm volatile("{\n.reg .pred p;\nmbarrier.test_wait.parity.shared::cta.b64 p, [%1], 0;\nselp.u32 %0, 1, 0, p;\n}"
                 : "=r"(done) : "r"(bar) : "memory");
    return done;
}
__device__ __forceinline__ void mbar_wait(uint32_t bar) {
    if (mbar_try(bar)) return;
    Watchdog wd;
    while (!mbar_try(bar)) wd.tick();
}
__device__ __forceinline__ bool mbar_try_cluster(uint32_t bar) {
    uint32_t done;
    asm volatile("{\n.reg .pred p;\nmbarrier.try_wait.parity.acquire.cluster.shared::cta.b64 p, [%1], 0;\nselp.u32 %0, 1, 0, p;\n}"
                 : "=r"(done) : "r"(bar) : "memory");
    return done;
}
__device__ __forceinline__ void mbar_wait_cluster(uint32_t bar) {
    if (mbar_try_cluster(bar)) return;
    Watchdog wd;
    while (!mbar_try_cluster(bar)) wd.tick();
}
__device__ __forceinline__ uint32_t mapa(uint32_t addr, uint32_t rank) {
    uint32_t r; asm("mapa.shared::cluster.u32 %0, %1, %2;" : "=r"(r) : "r"(addr), "r"(rank)); return r;
}
__device__ __forceinline__ void st_async2(uint32_t dst, uint32_t a, uint32_t b, uint32_t bar) {
    asm volatile("st.async.weak.shared::cluster.mbarrier::complete_tx::bytes.v2.b32 [%0], {%1,%2}, [%3];"
                 :: "r"(dst), "r"(a), "r"(b), "r"(bar) : "memory");
}
__device__ __forceinline__ void st_async4(uint32_t dst, uint32_t a, uint32_t b, uint32_t c, uint32_t d, uint32_t bar) {
    asm volatile("st.async.weak.shared::cluster.mbarrier::complete_tx::bytes.v4.b32 [%0], {%1,%2,%3,%4}, [%5];"
                 :: "r"(dst), "r"(a), "r"(b), "r"(c), "r"(d), "r"(bar) : "memory");
}
__device__ __forceinline__ void tma2d(uint32_t dst, const CUtensorMap* m, int c0, int c1, uint32_t bar) {
    asm volatile("cp.async.bulk.tensor.2d.shared::cluster.global.mbarrier::complete_tx::bytes [%0], [%1, {%3, %4}], [%2];"
                 :: "r"(dst), "l"(m), "r"(bar), "r"(c0), "r"(c1) : "memory");
}
__device__ __forceinline__ void tma3d(uint32_t dst, const CUtensorMap* m, int c0, int c1, int c2, uint32_t bar) {
    asm volatile("cp.async.bulk.tensor.3d.shared::cluster.global.mbarrier::complete_tx::bytes [%0], [%1, {%3, %4, %5}], [%2];"
                 :: "r"(dst), "l"(m), "r"(bar), "r"(c0), "r"(c1), "r"(c2) : "memory");
}
__device__ __forceinline__ void l2_prefetch(const void* src, uint32_t bytes) {
    asm volatile("cp.async.bulk.prefetch.L2.global [%0], %1;" :: "l"(src), "r"(bytes) : "memory");
}
__device__ __forceinline__ void ldsm4(uint32_t (&r)[4], uint32_t addr) {
    asm volatile("ldmatrix.sync.aligned.m8n8.x4.shared.b16 {%0,%1,%2,%3}, [%4];"
                 : "=r"(r[0]), "=r"(r[1]), "=r"(r[2]), "=r"(r[3]) : "r"(addr) : "memory");
}
__device__ __forceinline__ void ldsm4t(uint32_t (&r)[4], uint32_t addr) {
    asm volatile("ldmatrix.sync.aligned.m8n8.x4.trans.shared.b16 {%0,%1,%2,%3}, [%4];"
                 : "=r"(r[0]), "=r"(r[1]), "=r"(r[2]), "=r"(r[3]) : "r"(addr) : "memory");
}
__device__ __forceinline__ void mma16816(float (&d)[4], const uint32_t (&a)[4], uint32_t b0, uint32_t b1) {
    asm volatile("mma.sync.aligned.m16n8k16.row.col.f32.bf16.bf16.f32 {%0,%1,%2,%3}, {%4,%5,%6,%7}, {%8,%9}, {%0,%1,%2,%3};"
                 : "+f"(d[0]), "+f"(d[1]), "+f"(d[2]), "+f"(d[3])
                 : "r"(a[0]), "r"(a[1]), "r"(a[2]), "r"(a[3]), "r"(b0), "r"(b1));
}
__device__ __forceinline__ uint32_t movtrans(uint32_t a) {
    uint32_t d;
    asm volatile("movmatrix.sync.aligned.m8n8.trans.b16 %0, %1;" : "=r"(d) : "r"(a));
    return d;
}
__device__ __forceinline__ uint32_t pack_bf16(float lo, float hi) {
    uint32_t d;
    asm("cvt.rn.bf16x2.f32 %0, %1, %2;" : "=r"(d) : "f"(hi), "f"(lo));
    return d;
}
__device__ __forceinline__ float bf16r(float x) { return __bfloat162float(__float2bfloat16_rn(x)); }
__device__ __forceinline__ float bf_lo(uint32_t u) { return __uint_as_float(u << 16); }
__device__ __forceinline__ float bf_hi(uint32_t u) { return __uint_as_float(u & 0xffff0000u); }
__device__ __forceinline__ uint32_t hadd2_bf16(uint32_t a, uint32_t b) {
    uint32_t d;
    asm("add.rn.bf16x2 %0, %1, %2;" : "=r"(d) : "r"(a), "r"(b));
    return d;
}
__device__ __forceinline__ uint32_t ld_rlx(const uint32_t* p) {
    uint32_t v; asm volatile("ld.relaxed.gpu.global.u32 %0, [%1];" : "=r"(v) : "l"(p) : "memory"); return v;
}
__device__ __forceinline__ void st_rlx(uint32_t* p, uint32_t v) {
    asm volatile("st.relaxed.gpu.global.u32 [%0], %1;" :: "l"(p), "r"(v) : "memory");
}
__device__ __forceinline__ uint4 ld_rlx_2x64(const void* p) {
    unsigned long long a, b;
    asm volatile("ld.relaxed.gpu.global.v2.b64 {%0,%1}, [%2];" : "=l"(a), "=l"(b) : "l"(p) : "memory");
    return make_uint4((uint32_t)a, (uint32_t)(a >> 32), (uint32_t)b, (uint32_t)(b >> 32));
}
__device__ __forceinline__ void st_rlx_2x64(void* p, const uint4& v) {
    asm volatile("st.relaxed.gpu.global.v2.b64 [%0], {%1,%2};" :: "l"(p),
                 "l"(((unsigned long long)v.y << 32) | v.x), "l"(((unsigned long long)v.w << 32) | v.z) : "memory");
}
__device__ __forceinline__ void st_rlx_64(void* p, uint32_t lo, uint32_t hi) {
    asm volatile("st.relaxed.gpu.global.b64 [%0], %1;" :: "l"(p), "l"(((unsigned long long)hi << 32) | lo) : "memory");
}
__device__ __forceinline__ bool tagged(const uint4& v, uint32_t tag) { return (((v.x ^ tag) | (v.z ^ tag)) & 1u) == 0u; }
__device__ __forceinline__ void sts128(uint32_t a, uint32_t x, uint32_t y, uint32_t z, uint32_t w) {
    asm volatile("st.shared.v4.b32 [%0], {%1,%2,%3,%4};" :: "r"(a), "r"(x), "r"(y), "r"(z), "r"(w) : "memory");
}
template <typename T> __device__ __forceinline__ void pin64(T*& p) { asm volatile("" : "+l"(p)); }
__device__ __forceinline__ void pin32(uint32_t& v) { asm volatile("" : "+r"(v)); }
__device__ __forceinline__ void cbar() { asm volatile("bar.sync 1, 256;" ::: "memory"); }
__device__ __forceinline__ float ex2(float x) { float y; asm("ex2.approx.ftz.f32 %0, %1;" : "=f"(y) : "f"(x)); return y; }

__global__ void __launch_bounds__(NTHREADS, 2)
fused_decode_kernel(const __grid_constant__ Maps maps, const char* __restrict__ wq_raw, __nv_bfloat16* __restrict__ out)
{
    extern __shared__ __align__(1024) char smp[];
    const uint32_t sm = smem_u32(smp);
    const int tid = threadIdx.x, warp = tid >> 5, lane = tid & 31;
    const int cta = blockIdx.x, g = cta >> 4, c = cta & 15, b = c >> 1, half = c & 1;
    const bool ffn = g < 7;
    const uint32_t bar_full = sm + OFF_BAR, bar_empty = bar_full + NCHUNK * 8;
    const uint32_t bar_q = bar_empty + 16 * 8, bar_ml = bar_q + 8, bar_r = bar_q + 16, bar_x = bar_q + 24;

    if (warp == 8) {
        if (lane == 0) {
            mbar_init(bar_x, 1); mbar_init(bar_full, 1); mbar_init(bar_full + 8, 1);
            asm volatile("fence.proxy.async.shared::cta;" ::: "memory");
            mbar_expect(bar_full, CHUNK); tma2d(sm, &maps.wq, cta * 32, 0, bar_full);
            mbar_expect(bar_x, 8192); tma3d(sm + OFF_X, &maps.x, 0, 0, 0, bar_x);
            mbar_expect(bar_full + 8, CHUNK); tma2d(sm + CHUNK, &maps.wq, cta * 32, 256, bar_full + 8);
            if (sm & 1023u) __trap();
            #pragma unroll
            for (int s = 2; s < NCHUNK; s++) mbar_init(bar_full + s * 8, 1);
            #pragma unroll
            for (int s = 0; s < 16; s++) mbar_init(bar_empty + s * 8, (s < 2 || (s >= C_K && s < C_V)) ? 4 : 8);
            mbar_init(bar_q, 1); mbar_init(bar_ml, 1); mbar_init(bar_r, 1);
            mbar_expect(bar_q, 1024); mbar_expect(bar_ml, 32); mbar_expect(bar_r, 4096);
            asm volatile("fence.mbarrier_init.release.cluster;" ::: "memory");
            asm volatile("fence.proxy.async.shared::cta;" ::: "memory");
        }
        __syncwarp();
        asm volatile("barrier.cluster.arrive.relaxed.aligned;" ::: "memory");
        asm volatile("bar.arrive 2, %0;" :: "n"(NTHREADS) : "memory");
        if (lane == 0) {
            if (ffn) {
                mbar_expect(bar_full + 16, CHUNK);
                tma2d(sm + 2 * CHUNK, &maps.w1, cta * 16, 0, bar_full + 16);
                tma2d(sm + 2 * CHUNK + 8192, &maps.w1, cta * 16, 256, bar_full + 16);
            } else mbar_arrive(bar_full + 16);
            const int row0 = (b * 8 + g) * 4096 + 3072 + half * 512;
            uint32_t dst = sm + C_K * CHUNK;
            #pragma unroll 1
            for (int ch = C_K; ch < NCHUNK; ch++) {
                if (ch >= DEPTH) mbar_wait(bar_full + (ch < C_W2 ? ch - DEPTH : ch == C_W2 ? W2_AFTER : WO_AFTER) * 8);
                if (ch >= NSLOT) mbar_wait(bar_empty + (ch - NSLOT) * 8);
                const uint32_t bar = bar_full + ch * 8;
                if (ch < C_W2) {
                    mbar_expect(bar, CHUNK);
                    tma3d(dst, ch < C_V ? &maps.k : &maps.v, 0, row0 + ((ch - C_K) & 7) * 64, 0, bar);
                } else {
                    mbar_expect(bar, ch == C_W2 ? 14336 : CHUNK);
                    tma2d(dst, ch == C_W2 ? &maps.w2 : &maps.wo, g * 64,
                          ch == C_W2 ? c * 112 : c * 256 + (ch - C_WO) * 128, bar);
                }
                dst = (dst == sm + (NSLOT - 1) * CHUNK) ? sm : dst + CHUNK;
            }
        }
        __syncwarp();
        asm volatile("barrier.cluster.wait.aligned;" ::: "memory");
        return;
    }

    if (tid == 0) l2_prefetch(wq_raw + (size_t)cta * 32768, PF_BYTES);
    asm volatile("barrier.cluster.arrive.relaxed.aligned;" ::: "memory");
    const int gl = lane >> 2, t = lane & 3;
    float* lnst = reinterpret_cast<float*>(smp + OFF_STAT + 256);
    volatile uint32_t* epoch_s = reinterpret_cast<volatile uint32_t*>(smp + OFF_STAT + 320);
    const int ru = lane & 7, rp = lane >> 3;
    const int ob = 2 * (ru & 3) + (rp & 1);
    const int ocol = g * 64 + (c >> 2) * 16 + 2 * (c & 3) + (ru >> 2) + 8 * (rp >> 1);
    uint32_t epoch_r = 0;
    if (tid == 64) epoch_r = ld_rlx(&g_epoch);
    asm volatile("bar.sync 2, %0;" :: "n"(NTHREADS) : "memory");
    if (tid == 64) *epoch_s = epoch_r;
    mbar_wait(bar_x);
    uint32_t xf[8];
    #pragma unroll
    for (int j = 0; j < 8; j++)
        xf[j] = *reinterpret_cast<const uint32_t*>(smp + OFF_X + warp * 1024 + gl * 128 + ((j ^ gl) << 4) + t * 4);
    const float resid = __bfloat162float(*reinterpret_cast<const __nv_bfloat16*>(
        smp + OFF_X + g * 1024 + ob * 128 + ((((ocol >> 3) & 7) ^ ob) << 4) + (ocol & 7) * 2));
    {
        const char* xr = smp + OFF_X + (lane >> 3) * 1024 + warp * 128 + (lane & 7) * 16;
        const uint4 xa = *reinterpret_cast<const uint4*>(xr), xb = *reinterpret_cast<const uint4*>(xr + 4096);
        const float sh = bf_lo(*reinterpret_cast<const uint32_t*>(smp + OFF_X + warp * 128));
        const uint32_t w[8] = {xa.x, xa.y, xa.z, xa.w, xb.x, xb.y, xb.z, xb.w};
        float s4[4] = {}, q4[4] = {};
        #pragma unroll
        for (int j = 0; j < 8; j++) {
            const float lo = bf_lo(w[j]) - sh, hi = bf_hi(w[j]) - sh;
            s4[j & 3] += lo + hi;
            q4[j & 3] = fmaf(lo, lo, fmaf(hi, hi, q4[j & 3]));
        }
        float s = (s4[0] + s4[1]) + (s4[2] + s4[3]), q2 = (q4[0] + q4[1]) + (q4[2] + q4[3]);
        #pragma unroll
        for (int o = 16; o > 0; o >>= 1) {
            s += __shfl_xor_sync(0xffffffffu, s, o);
            q2 += __shfl_xor_sync(0xffffffffu, q2, o);
        }
        const float ms = s * (1.f / 512.f), mean = sh + ms;
        q2 = fmaxf(fmaf(-ms, s, q2), 0.f);
        const float den = bf16r(__fsqrt_rn(bf16r(bf16r(q2 * (1.f / 512.f)) + 1e-5f)));
        if (lane == 0) *reinterpret_cast<float2*>(lnst + warp * 2) = make_float2(bf16r(mean), __frcp_rn(den));
    }
    cbar();
    {
        const float2 st = *reinterpret_cast<const float2*>(lnst + gl * 2);
        #pragma unroll
        for (int j = 0; j < 8; j++)
            xf[j] = pack_bf16(bf16r(bf_lo(xf[j]) - st.x) * st.y, bf16r(bf_hi(xf[j]) - st.x) * st.y);
    }
    const uint32_t tag = (*epoch_s + 1u) & 1u;

    float* red = reinterpret_cast<float*>(smp + OFF_RED);
    const int mj = lane >> 3, mr = lane & 7;
    float* r0 = red + (warp * 8 + 2 * t) * RED_PITCH + gl;
    {
        float aq[2][4] = {};
        mbar_wait(bar_full + (warp >> 2) * 8);
        const uint32_t wqs = sm + (warp >> 2) * CHUNK;
        #pragma unroll
        for (int s = 0; s < 4; s++) {
            const int row = (warp & 3) * 64 + s * 16 + (mj >> 1) * 8 + mr;
            #pragma unroll
            for (int j = 0; j < 2; j++) {
                uint32_t a[4];
                ldsm4t(a, wqs + row * 64 + (((2 * j + (mj & 1)) ^ ((row >> 1) & 3)) << 4));
                mma16816(aq[j], a, xf[2 * s], xf[2 * s + 1]);
            }
        }
        __syncwarp();
        if (lane == 0) mbar_arrive(bar_empty + (warp >> 2) * 8);
        #pragma unroll
        for (int j = 0; j < 2; j++) {
            r0[j * 16] = aq[j][0]; r0[RED_PITCH + j * 16] = aq[j][1];
            r0[j * 16 + 8] = aq[j][2]; r0[RED_PITCH + j * 16 + 8] = aq[j][3];
        }
    }
    cbar();
    asm volatile("barrier.cluster.wait.aligned;" ::: "memory");
    if (warp < 4) {
        const int bb = tid >> 4, wd = tid & 15;
        const int col = (wd >> 3) * 16 + ((wd >> 1) & 3) * 2 + (wd & 1) * 8;
        float s0 = 0.f, s1 = 0.f;
        #pragma unroll
        for (int w = 0; w < 8; w++) {
            const float2 f = *reinterpret_cast<const float2*>(red + (w * 8 + bb) * RED_PITCH + col);
            s0 += f.x; s1 += f.y;
        }
        const uint32_t u = pack_bf16(s0, s1);
        const int q0 = (lane & 16) + (lane & 3) * 4;
        const uint32_t u0 = __shfl_sync(0xffffffffu, u, q0), u1 = __shfl_sync(0xffffffffu, u, q0 + 1);
        const uint32_t u2 = __shfl_sync(0xffffffffu, u, q0 + 2), u3 = __shfl_sync(0xffffffffu, u, q0 + 3);
        if (wd < 8) {
            const uint32_t rank = 2 * bb + (wd >> 2);
            st_async4(mapa(sm + OFF_Q + c * 64 + (wd & 3) * 16, rank), u0, u1, u2, u3, mapa(bar_q, rank));
        }
    }
    if (ffn) {
        float ah[4] = {};
        mbar_wait(bar_full + 2 * 8);
        const uint32_t w1s = sm + 2 * CHUNK;
        #pragma unroll
        for (int s = 0; s < 4; s++) {
            const int row = warp * 64 + s * 16 + (mj >> 1) * 8 + mr;
            uint32_t a[4];
            ldsm4t(a, w1s + row * 32 + (((mj & 1) ^ ((row >> 2) & 1)) << 4));
            mma16816(ah, a, xf[2 * s], xf[2 * s + 1]);
        }
        __syncwarp();
        if (lane == 0) mbar_arrive(bar_empty + 2 * 8);
        cbar();
        r0[0] = ah[0]; r0[RED_PITCH] = ah[1]; r0[8] = ah[2]; r0[RED_PITCH + 8] = ah[3];
        cbar();
        if (warp >= 6) {
            const int bb = (tid & 63) >> 3, wd = tid & 7;
            float s0 = 0.f, s1 = 0.f;
            #pragma unroll
            for (int w = 0; w < 8; w++) {
                const float2 f = *reinterpret_cast<const float2*>(red + (w * 8 + bb) * RED_PITCH + 2 * wd);
                s0 += f.x; s1 += f.y;
            }
            s0 = bf16r(s0); s1 = bf16r(s1);
            s0 = __fdividef(s0, 1.f + __expf(-s0)); s1 = __fdividef(s1, 1.f + __expf(-s1));
            const uint32_t u = pack_bf16(s0, s1);
            const uint32_t un = __shfl_down_sync(0xffffffffu, u, 1);
            if (!(wd & 1)) st_rlx_64(g_h + bb * 896 + cta * 8 + wd, (u & ~1u) | tag, un);
        }
    } else {
        __syncwarp();
        if (lane == 0) mbar_arrive(bar_empty + 2 * 8);
    }

    float sc[4][4];
    float m0 = -INFINITY, m1 = -INFINITY;
    {
        mbar_wait_cluster(bar_q);
        uint32_t qb[8][2];
        #pragma unroll
        for (int s = 0; s < 8; s++) {
            const uint2 v = *reinterpret_cast<const uint2*>(smp + OFF_Q + (((gl & 3) * 8 + s) * 4 + t) * 8);
            qb[s][0] = v.x; qb[s][1] = v.y;
        }
        const uint32_t koff = ((warp & 3) * 16 + (mj & 1) * 8 + mr) * 128;
        #pragma unroll
        for (int i = 0; i < 4; i++) {
            const int ck = C_K + 2 * i + (warp >> 2);
            mbar_wait(bar_full + ck * 8);
            const uint32_t ks = sm + (ck % NSLOT) * CHUNK + koff;
            float s0[4] = {}, s1[4] = {};
            #pragma unroll
            for (int s = 0; s < 4; s++) {
                const uint32_t sw = ((2 * s + (mj >> 1)) ^ mr) << 4;
                uint32_t a[4], a2[4];
                ldsm4(a, ks + sw);
                ldsm4(a2, ks + 8192 + sw);
                mma16816(s0, a, qb[s][0], qb[s][1]);
                mma16816(s1, a2, qb[4 + s][0], qb[4 + s][1]);
            }
            __syncwarp();
            if (lane == 0) mbar_arrive(bar_empty + ck * 8);
            #pragma unroll
            for (int k = 0; k < 4; k++) sc[i][k] = bf16r(bf16r(s0[k] + s1[k]) * 0.08838834764831845f);
            m0 = fmaxf(m0, fmaxf(sc[i][0], sc[i][2]));
            m1 = fmaxf(m1, fmaxf(sc[i][1], sc[i][3]));
        }
    }
    float* wmax = reinterpret_cast<float*>(smp + OFF_STAT);
    float* wsum = wmax + 32;
    constexpr float L2E = 1.4426950408889634f;
    {
        #pragma unroll
        for (int o = 4; o < 32; o <<= 1) {
            m0 = fmaxf(m0, __shfl_xor_sync(0xffffffffu, m0, o));
            m1 = fmaxf(m1, __shfl_xor_sync(0xffffffffu, m1, o));
        }
        if (lane < 2) *reinterpret_cast<float2*>(wmax + warp * 4 + 2 * lane) = make_float2(m0, m1);
        cbar();
        #pragma unroll
        for (int w = 0; w < 8; w++) {
            const float2 f = *reinterpret_cast<const float2*>(wmax + w * 4 + 2 * (t & 1));
            m0 = fmaxf(m0, f.x); m1 = fmaxf(m1, f.y);
        }
        float l0 = 0.f, l1 = 0.f;
        uint32_t pw[4][2];
        #pragma unroll
        for (int i = 0; i < 4; i++) {
            const float p0 = ex2((sc[i][0] - m0) * L2E), p1 = ex2((sc[i][1] - m1) * L2E);
            const float p2 = ex2((sc[i][2] - m0) * L2E), p3 = ex2((sc[i][3] - m1) * L2E);
            l0 += p0 + p2; l1 += p1 + p3;
            pw[i][0] = movtrans(pack_bf16(p0, p1));
            pw[i][1] = movtrans(pack_bf16(p2, p3));
        }
        if (lane < 16) {
            char* pd = smp + OFF_P + ((warp >> 2) * 2 + ((warp >> 1) & 1)) * 256 + lane * 16 + (warp & 1) * 8;
            #pragma unroll
            for (int i = 0; i < 4; i++) *reinterpret_cast<uint2*>(pd + i * 1024) = make_uint2(pw[i][0], pw[i][1]);
        }
        #pragma unroll
        for (int o = 4; o < 32; o <<= 1) {
            l0 += __shfl_xor_sync(0xffffffffu, l0, o);
            l1 += __shfl_xor_sync(0xffffffffu, l1, o);
        }
        if (lane < 2) *reinterpret_cast<float2*>(wsum + warp * 4 + 2 * lane) = make_float2(l0, l1);
    }
    cbar();
    float l0 = 0.f, l1 = 0.f;
    #pragma unroll
    for (int w = 0; w < 8; w++) {
        const float2 f = *reinterpret_cast<const float2*>(wsum + w * 4 + 2 * (t & 1));
        l0 += f.x; l1 += f.y;
    }
    if (tid < 2) {
        const uint32_t dst = mapa(sm + OFF_ML + tid * 8, c ^ 1), bar = mapa(bar_ml, c ^ 1);
        st_async2(dst, __float_as_uint(m0), __float_as_uint(m1), bar);
        st_async2(dst + 16, __float_as_uint(l0), __float_as_uint(l1), bar);
    }

    const uint32_t* op = g_o + (((tid >> 4) & 7) * 32 + 2 * c + (tid >> 7)) * 64 + (tid & 15) * 4;
    uint32_t* opub = g_o + ((half * 8 + b) * 32 + g * 4) * 64 + (tid & 63) * 4;
    __nv_bfloat16* outp = out + ob * 512 + ocol;
    uint32_t s_ost = sm + OFF_OST + gl * 256 + (t * 4 + ((warp >> 1) ^ (t & 2))) * 16 + (warp & 1) * 8;
    uint32_t s_rdst = mapa(sm + OFF_RIN + (c * 2 + (warp >> 2)) * 128 + ru * 16, (warp & 3) * 4 + rp);
    uint32_t s_rbar = mapa(bar_r, (warp & 3) * 4 + rp);
    uint32_t s_obw = sm + OFF_OB + (tid >> 4) * 320 + (((tid & 15) ^ ((tid >> 4) & 1)) << 4);
    uint32_t s_obr = sm + OFF_OB + gl * 320 + t * 64 + ((((warp >> 2) * 2) ^ (t & 2) ^ (gl & 1)) << 4);
    const int hb = min(tid / 14, 7), hpc = tid - (tid / 14) * 14;
    const uint32_t* hp = g_h + hb * 896 + c * 56 + hpc * 4;
    uint32_t s_h = sm + OFF_H + hb * 272 + hpc * 16;
    pin64(op); pin64(opub); pin64(outp); pin64(hp);
    uint32_t aoff = sm + (warp >> 2) * 8192 + ((mj >> 1) * 8 + mr) * 128 + (((2 * (warp & 3) + (mj & 1)) ^ mr) << 4);
    uint32_t s_hs = sm + OFF_H + (gl * 68 + (warp >> 2) * 32 + t) * 4;
    uint32_t s_rin = sm + OFF_RIN + lane * 16;
    uint32_t ptid = tid;
    pin32(s_ost); pin32(s_rdst); pin32(s_rbar); pin32(s_obw); pin32(s_obr); pin32(s_h);
    pin32(aoff); pin32(s_hs); pin32(s_rin); pin32(ptid);
    uint4 hv = make_uint4(tag, 0u, tag, 0u);
    if (tid < 112) hv = ld_rlx_2x64(hp);
    if (tid < 64) st_rlx_2x64(opub, make_uint4(tag ^ 1u, 0u, tag ^ 1u, 0u));

    float f0 = 0.f, f1 = 0.f;
    float oc[4][4] = {};
    {
        const int ach = 2 * warp + (mj & 1);
        uint32_t voff = (ach >> 3) * 8192 + ((mj >> 1) * 8 + mr) * 128 + (((ach & 7) ^ mr) << 4);
        pin32(voff);
        const uint4* pfp = reinterpret_cast<const uint4*>(smp + OFF_P) + (lane & 15);
        uint32_t vs = sm + (C_V % NSLOT) * CHUNK;
        #pragma unroll 1
        for (int j = 0; j < 8; j++) {
            const uint4 pa = pfp[j * 32], pb = pfp[j * 32 + 16];
            if (j == 6) {
                if (!tagged(hv, tag)) {
                    Watchdog wd;
                    do { hv = ld_rlx_2x64(hp); wd.tick(); } while (!tagged(hv, tag));
                }
                if (tid < 112) sts128(s_h, hv.x, hv.y, hv.z, hv.w);
                __syncwarp();
                mbar_wait_cluster(bar_ml);
                const float* pm = reinterpret_cast<const float*>(smp + OFF_ML) + (t & 1) * 2;
                const float mo0 = pm[0], mo1 = pm[1];
                const float mt0 = fmaxf(m0, mo0), mt1 = fmaxf(m1, mo1);
                const float e0 = ex2((m0 - mt0) * L2E), e1 = ex2((m1 - mt1) * L2E);
                f0 = __fdividef(e0, l0 * e0 + pm[4] * ex2((mo0 - mt0) * L2E));
                f1 = __fdividef(e1, l1 * e1 + pm[5] * ex2((mo1 - mt1) * L2E));
            }
            mbar_wait(bar_full + (C_V + j) * 8);
            uint32_t a[4][4];
            #pragma unroll
            for (int s = 0; s < 4; s++) ldsm4t(a[s], vs + voff + s * 2048);
            mma16816(oc[0], a[0], pa.x, pa.y);
            mma16816(oc[1], a[1], pa.z, pa.w);
            mma16816(oc[2], a[2], pb.x, pb.y);
            mma16816(oc[3], a[3], pb.z, pb.w);
            __syncwarp();
            if (j < 5 && lane == 0) mbar_arrive(bar_empty + (C_V + j) * 8);
            vs = (vs == sm + (NSLOT - 1) * CHUNK) ? sm : vs + CHUNK;
        }
    }
    {
        const float o0 = (oc[0][0] + oc[1][0]) + (oc[2][0] + oc[3][0]);
        const float o1 = (oc[0][1] + oc[1][1]) + (oc[2][1] + oc[3][1]);
        const float o2 = (oc[0][2] + oc[1][2]) + (oc[2][2] + oc[3][2]);
        const float o3 = (oc[0][3] + oc[1][3]) + (oc[2][3] + oc[3][3]);
        const uint32_t u0 = movtrans(pack_bf16(o0 * f0, o1 * f1));
        const uint32_t u1 = movtrans(pack_bf16(o2 * f0, o3 * f1));
        if (!(ptid & 16))
            asm volatile("st.shared.v2.b32 [%0], {%1,%2};" :: "r"(s_ost), "r"((u0 & ~1u) | tag), "r"(u1) : "memory");
        cbar();
        if (ptid < 64) st_rlx_2x64(opub, *reinterpret_cast<const uint4*>(smp + OFF_OST + ptid * 16));
    }

    {
        float ac[4][4] = {};
        mbar_wait(bar_full + C_W2 * 8);
        uint4 oa = ld_rlx_2x64(op), obv = ld_rlx_2x64(op + 16384);
        #pragma unroll
        for (int s = 0; s < 4; s++) {
            if (s < 3 || ptid < 128) {
                uint32_t a[4], h0, h1;
                ldsm4t(a, aoff + (C_W2 % NSLOT) * CHUNK + s * 2048);
                asm volatile("ld.shared.b32 %0, [%1];" : "=r"(h0) : "r"(s_hs + s * 32) : "memory");
                asm volatile("ld.shared.b32 %0, [%1];" : "=r"(h1) : "r"(s_hs + s * 32 + 16) : "memory");
                mma16816(ac[s], a, h0, h1);
            }
        }
        uint32_t wa[8][4];
        bool have0 = false, have1 = false;
        auto wo_part = [&](int i) {
            #pragma unroll
            for (int s = 0; s < 4; s++) ldsm4t(wa[i * 4 + s], aoff + (C_WO % NSLOT + i) * CHUNK + s * 2048);
        };
        Watchdog wd;
        for (;;) {
            if (!have0 && mbar_test(bar_full + C_WO * 8)) { have0 = true; wo_part(0); }
            if (!have1 && mbar_test(bar_full + (C_WO + 1) * 8)) { have1 = true; wo_part(1); }
            wd.tick();
            const bool na = !tagged(oa, tag), nb = !tagged(obv, tag);
            if (!__any_sync(0xffffffffu, na || nb)) break;
            if (na) oa = ld_rlx_2x64(op);
            if (nb) obv = ld_rlx_2x64(op + 16384);
        }
        sts128(s_obw, hadd2_bf16(oa.x, obv.x), hadd2_bf16(oa.y, obv.y), hadd2_bf16(oa.z, obv.z), hadd2_bf16(oa.w, obv.w));
        cbar();
        uint4 of[4];
        #pragma unroll
        for (int i = 0; i < 4; i++)
            asm volatile("ld.shared.v4.b32 {%0,%1,%2,%3}, [%4];" : "=r"(of[i].x), "=r"(of[i].y), "=r"(of[i].z), "=r"(of[i].w)
                         : "r"((s_obr ^ ((i & 1) << 4)) + (i >> 1) * 2560) : "memory");
        if (!have0) { mbar_wait(bar_full + C_WO * 8); wo_part(0); }
        mma16816(ac[0], wa[0], of[0].x, of[0].y);
        mma16816(ac[1], wa[1], of[0].z, of[0].w);
        mma16816(ac[2], wa[2], of[1].x, of[1].y);
        mma16816(ac[3], wa[3], of[1].z, of[1].w);
        if (!have1) { mbar_wait(bar_full + (C_WO + 1) * 8); wo_part(1); }
        mma16816(ac[0], wa[4], of[2].x, of[2].y);
        mma16816(ac[1], wa[5], of[2].z, of[2].w);
        mma16816(ac[2], wa[6], of[3].x, of[3].y);
        mma16816(ac[3], wa[7], of[3].z, of[3].w);
        st_async4(s_rdst,
                  __float_as_uint((ac[0][0] + ac[1][0]) + (ac[2][0] + ac[3][0])),
                  __float_as_uint((ac[0][1] + ac[1][1]) + (ac[2][1] + ac[3][1])),
                  __float_as_uint((ac[0][2] + ac[1][2]) + (ac[2][2] + ac[3][2])),
                  __float_as_uint((ac[0][3] + ac[1][3]) + (ac[2][3] + ac[3][3])), s_rbar);
    }

    if (ptid < 32) {
        mbar_wait_cluster(bar_r);
        float4 v[8];
        #pragma unroll
        for (int i = 0; i < 8; i++)
            asm volatile("ld.shared.v4.f32 {%0,%1,%2,%3}, [%4];" : "=f"(v[i].x), "=f"(v[i].y), "=f"(v[i].z), "=f"(v[i].w)
                         : "r"(s_rin + i * 512) : "memory");
        const float s0 = ((v[0].x + v[1].x) + (v[2].x + v[3].x)) + ((v[4].x + v[5].x) + (v[6].x + v[7].x));
        const float s1 = ((v[0].y + v[1].y) + (v[2].y + v[3].y)) + ((v[4].y + v[5].y) + (v[6].y + v[7].y));
        const float s2 = ((v[0].z + v[1].z) + (v[2].z + v[3].z)) + ((v[4].z + v[5].z) + (v[6].z + v[7].z));
        const float s3 = ((v[0].w + v[1].w) + (v[2].w + v[3].w)) + ((v[4].w + v[5].w) + (v[6].w + v[7].w));
        const bool p1 = ptid & 8, p2 = ptid & 16;
        float a = p1 ? s1 : s0, bq = p1 ? s3 : s2;
        a += __shfl_xor_sync(0xffffffffu, p1 ? s0 : s1, 8);
        bq += __shfl_xor_sync(0xffffffffu, p1 ? s2 : s3, 8);
        float r = p2 ? bq : a;
        r += __shfl_xor_sync(0xffffffffu, p2 ? a : bq, 16);
        *outp = __float2bfloat16_rn(r + resid);
        if (cta == 0 && lane == 0) st_rlx(&g_epoch, *epoch_s + 1u);
    }
}

typedef CUresult (*EncodeFn)(CUtensorMap*, CUtensorMapDataType, cuuint32_t, void*, const cuuint64_t*, const cuuint64_t*,
                             const cuuint32_t*, const cuuint32_t*, CUtensorMapInterleave, CUtensorMapSwizzle,
                             CUtensorMapL2promotion, CUtensorMapFloatOOBfill);

void encode(EncodeFn fn, CUtensorMap* m, const void* p, int rank, const cuuint64_t* dims, const cuuint64_t* strides,
            const cuuint32_t* box, CUtensorMapSwizzle sw) {
    const cuuint32_t es[3] = {1, 1, 1};
    fn(m, CU_TENSOR_MAP_DATA_TYPE_BFLOAT16, rank, const_cast<void*>(p), dims, strides, box, es,
       CU_TENSOR_MAP_INTERLEAVE_NONE, sw, CU_TENSOR_MAP_L2_PROMOTION_L2_256B, CU_TENSOR_MAP_FLOAT_OOB_FILL_NONE);
}

}

extern "C" void kernel_launch(void* const* d_in, const int* in_sizes, int n_in, void* d_out, int out_size) {
    (void)in_sizes; (void)n_in; (void)out_size;
    static EncodeFn fn = nullptr;
    if (!fn) {
        cudaDriverEntryPointQueryResult qr;
        cudaGetDriverEntryPoint("cuTensorMapEncodeTiled", (void**)&fn, cudaEnableDefault, &qr);
        cudaFuncSetAttribute(fused_decode_kernel, cudaFuncAttributeMaxDynamicSharedMemorySize, SMEM_BYTES);
        cudaFuncSetAttribute(fused_decode_kernel, cudaFuncAttributeNonPortableClusterSizeAllowed, 1);
    }
    Maps m;
    {
        const cuuint64_t d[3] = {64, 64ull * 4096, 2}, s[2] = {256, 128};
        const cuuint32_t bx[3] = {64, 64, 2};
        encode(fn, &m.k, d_in[1], 3, d, s, bx, CU_TENSOR_MAP_SWIZZLE_128B);
        encode(fn, &m.v, d_in[2], 3, d, s, bx, CU_TENSOR_MAP_SWIZZLE_128B);
    }
    { const cuuint64_t d[3] = {64, 8, 8}, s[2] = {1024, 128}; const cuuint32_t bx[3] = {64, 8, 8};
      encode(fn, &m.x, d_in[0], 3, d, s, bx, CU_TENSOR_MAP_SWIZZLE_128B); }
    { const cuuint64_t d[2] = {4096, 512}, s[1] = {8192}; const cuuint32_t bx[2] = {32, 256};
      encode(fn, &m.wq, d_in[3], 2, d, s, bx, CU_TENSOR_MAP_SWIZZLE_64B); }
    { const cuuint64_t d[2] = {512, 4096}, s[1] = {1024}; const cuuint32_t bx[2] = {64, 128};
      encode(fn, &m.wo, d_in[4], 2, d, s, bx, CU_TENSOR_MAP_SWIZZLE_128B); }
    { const cuuint64_t d[2] = {1792, 512}, s[1] = {3584}; const cuuint32_t bx[2] = {16, 256};
      encode(fn, &m.w1, d_in[6], 2, d, s, bx, CU_TENSOR_MAP_SWIZZLE_32B); }
    { const cuuint64_t d[2] = {512, 1792}, s[1] = {1024}; const cuuint32_t bx[2] = {64, 112};
      encode(fn, &m.w2, d_in[7], 2, d, s, bx, CU_TENSOR_MAP_SWIZZLE_128B); }

    cudaLaunchConfig_t cfg = {};
    cfg.gridDim = dim3(NCTA); cfg.blockDim = dim3(NTHREADS); cfg.dynamicSmemBytes = SMEM_BYTES;
    cfg.stream = cudaStreamPerThread;
    cudaLaunchAttribute at[2];
    at[0].id = cudaLaunchAttributeClusterDimension;
    at[0].val.clusterDim.x = CLUSTER; at[0].val.clusterDim.y = 1; at[0].val.clusterDim.z = 1;
    at[1].id = cudaLaunchAttributeClusterSchedulingPolicyPreference;
    at[1].val.clusterSchedulingPolicyPreference = cudaClusterSchedulingPolicyLoadBalancing;
    cfg.attrs = at; cfg.numAttrs = 2;
    cudaLaunchKernelEx(&cfg, fused_decode_kernel, m, (const char*)d_in[3], (__nv_bfloat16*)d_out);
}
```

```cpp
#include <cuda_runtime.h>
#include <cuda_bf16.h>
#include <cuda.h>
#include <stdint.h>

namespace {

constexpr int NCTA = 128;
constexpr int CLUSTER = 16;
constexpr int NTHREADS = 288;
constexpr int CHUNK = 16384;
constexpr int NSLOT = 6;
constexpr int NCHUNK = 22;
constexpr int C_K = 3, C_V = 11, C_W2 = 19, C_WO = 20;
constexpr int DEPTH = 4;
constexpr int W2_AFTER = 16;
constexpr int WO_AFTER = 18;
constexpr int PF_BYTES = 8192;

constexpr int RED_PITCH = 36;
constexpr int OFF_U = NSLOT * CHUNK;
constexpr int OFF_X = OFF_U;
constexpr int OFF_RED = OFF_U;
constexpr int OFF_P = OFF_U;
constexpr int OFF_OB = OFF_U + 4096;
constexpr int OFF_RIN = OFF_U + 9216;
constexpr int OFF_Q = OFF_RIN + 4096;
constexpr int OFF_OST = OFF_Q;
constexpr int OFF_H = OFF_Q + 1024;
constexpr int OFF_ML = OFF_H + 2176;
constexpr int OFF_STAT = OFF_ML + 32;
constexpr int OFF_BAR = OFF_STAT + 336;
constexpr int SMEM_BYTES = OFF_BAR + 42 * 8;
static_assert(2 * (SMEM_BYTES + 1024) <= 233472, "two CTAs per SM");

struct Maps { CUtensorMap x, wq, k, v, w1, wo, w2; };

__device__ unsigned int g_epoch;
__device__ __align__(128) uint32_t g_o[2 * 8 * 32 * 64];
__device__ __align__(128) uint32_t g_h[8 * 896];

constexpr uint32_t BAR_LIMIT = 1u << 20, POLL_LIMIT = 1u << 23;

__device__ __forceinline__ uint32_t smem_u32(const void* p) { return (uint32_t)__cvta_generic_to_shared(p); }
__device__ __forceinline__ void mbar_init(uint32_t bar, uint32_t cnt) {
    asm volatile("mbarrier.init.shared::cta.b64 [%0], %1;" :: "r"(bar), "r"(cnt) : "memory");
}
__device__ __forceinline__ void mbar_expect(uint32_t bar, uint32_t bytes) {
    asm volatile("mbarrier.arrive.expect_tx.shared::cta.b64 _, [%0], %1;" :: "r"(bar), "r"(bytes) : "memory");
}
__device__ __forceinline__ void mbar_arrive(uint32_t bar) {
    asm volatile("mbarrier.arrive.shared::cta.b64 _, [%0];" :: "r"(bar) : "memory");
}
__device__ __forceinline__ bool mbar_try(uint32_t bar) {
    uint32_t done;
    asm volatile("{\n.reg .pred p;\nmbarrier.try_wait.parity.shared::cta.b64 p, [%1], 0;\nselp.u32 %0, 1, 0, p;\n}"
                 : "=r"(done) : "r"(bar) : "memory");
    return done;
}
__device__ __forceinline__ bool mbar_test(uint32_t bar) {
    uint32_t done;
    asm volatile("{\n.reg .pred p;\nmbarrier.test_wait.parity.shared::cta.b64 p, [%1], 0;\nselp.u32 %0, 1, 0, p;\n}"
                 : "=r"(done) : "r"(bar) : "memory");
    return done;
}
__device__ __forceinline__ void mbar_wait(uint32_t bar) {
    for (uint32_t n = 0; !mbar_try(bar); ) if (++n > BAR_LIMIT) __trap();
}
__device__ __forceinline__ bool mbar_try_cluster(uint32_t bar) {
    uint32_t done;
    asm volatile("{\n.reg .pred p;\nmbarrier.try_wait.parity.acquire.cluster.shared::cta.b64 p, [%1], 0;\nselp.u32 %0, 1, 0, p;\n}"
                 : "=r"(done) : "r"(bar) : "memory");
    return done;
}
__device__ __forceinline__ void mbar_wait_cluster(uint32_t bar) {
    for (uint32_t n = 0; !mbar_try_cluster(bar); ) if (++n > BAR_LIMIT) __trap();
}
__device__ __forceinline__ uint32_t mapa(uint32_t addr, uint32_t rank) {
    uint32_t r; asm("mapa.shared::cluster.u32 %0, %1, %2;" : "=r"(r) : "r"(addr), "r"(rank)); return r;
}
__device__ __forceinline__ void st_async2(uint32_t dst, uint32_t a, uint32_t b, uint32_t bar) {
    asm volatile("st.async.weak.shared::cluster.mbarrier::complete_tx::bytes.v2.b32 [%0], {%1,%2}, [%3];"
                 :: "r"(dst), "r"(a), "r"(b), "r"(bar) : "memory");
}
__device__ __forceinline__ void st_async4(uint32_t dst, uint32_t a, uint32_t b, uint32_t c, uint32_t d, uint32_t bar) {
    asm volatile("st.async.weak.shared::cluster.mbarrier::complete_tx::bytes.v4.b32 [%0], {%1,%2,%3,%4}, [%5];"
                 :: "r"(dst), "r"(a), "r"(b), "r"(c), "r"(d), "r"(bar) : "memory");
}
__device__ __forceinline__ void tma2d(uint32_t dst, const CUtensorMap* m, int c0, int c1, uint32_t bar) {
    asm volatile("cp.async.bulk.tensor.2d.shared::cluster.global.mbarrier::complete_tx::bytes [%0], [%1, {%3, %4}], [%2];"
                 :: "r"(dst), "l"(m), "r"(bar), "r"(c0), "r"(c1) : "memory");
}
__device__ __forceinline__ void tma3d(uint32_t dst, const CUtensorMap* m, int c0, int c1, int c2, uint32_t bar) {
    asm volatile("cp.async.bulk.tensor.3d.shared::cluster.global.mbarrier::complete_tx::bytes [%0], [%1, {%3, %4, %5}], [%2];"
                 :: "r"(dst), "l"(m), "r"(bar), "r"(c0), "r"(c1), "r"(c2) : "memory");
}
__device__ __forceinline__ void l2_prefetch(const void* src, uint32_t bytes) {
    asm volatile("cp.async.bulk.prefetch.L2.global [%0], %1;" :: "l"(src), "r"(bytes) : "memory");
}
__device__ __forceinline__ void ldsm4(uint32_t (&r)[4], uint32_t addr) {
    asm volatile("ldmatrix.sync.aligned.m8n8.x4.shared.b16 {%0,%1,%2,%3}, [%4];"
                 : "=r"(r[0]), "=r"(r[1]), "=r"(r[2]), "=r"(r[3]) : "r"(addr) : "memory");
}
__device__ __forceinline__ void ldsm4t(uint32_t (&r)[4], uint32_t addr) {
    asm volatile("ldmatrix.sync.aligned.m8n8.x4.trans.shared.b16 {%0,%1,%2,%3}, [%4];"
                 : "=r"(r[0]), "=r"(r[1]), "=r"(r[2]), "=r"(r[3]) : "r"(addr) : "memory");
}
__device__ __forceinline__ void mma16816(float (&d)[4], const uint32_t (&a)[4], uint32_t b0, uint32_t b1) {
    asm volatile("mma.sync.aligned.m16n8k16.row.col.f32.bf16.bf16.f32 {%0,%1,%2,%3}, {%4,%5,%6,%7}, {%8,%9}, {%0,%1,%2,%3};"
                 : "+f"(d[0]), "+f"(d[1]), "+f"(d[2]), "+f"(d[3])
                 : "r"(a[0]), "r"(a[1]), "r"(a[2]), "r"(a[3]), "r"(b0), "r"(b1));
}
__device__ __forceinline__ uint32_t movtrans(uint32_t a) {
    uint32_t d;
    asm volatile("movmatrix.sync.aligned.m8n8.trans.b16 %0, %1;" : "=r"(d) : "r"(a));
    return d;
}
__device__ __forceinline__ uint32_t pack_bf16(float lo, float hi) {
    uint32_t d;
    asm("cvt.rn.bf16x2.f32 %0, %1, %2;" : "=r"(d) : "f"(hi), "f"(lo));
    return d;
}
__device__ __forceinline__ float bf16r(float x) { return __bfloat162float(__float2bfloat16_rn(x)); }
__device__ __forceinline__ float bf_lo(uint32_t u) { return __uint_as_float(u << 16); }
__device__ __forceinline__ float bf_hi(uint32_t u) { return __uint_as_float(u & 0xffff0000u); }
__device__ __forceinline__ uint32_t hadd2_bf16(uint32_t a, uint32_t b) {
    uint32_t d;
    asm("add.rn.bf16x2 %0, %1, %2;" : "=r"(d) : "r"(a), "r"(b));
    return d;
}
__device__ __forceinline__ uint32_t ld_rlx(const uint32_t* p) {
    uint32_t v; asm volatile("ld.relaxed.gpu.global.u32 %0, [%1];" : "=r"(v) : "l"(p) : "memory"); return v;
}
__device__ __forceinline__ void st_rlx(uint32_t* p, uint32_t v) {
    asm volatile("st.relaxed.gpu.global.u32 [%0], %1;" :: "l"(p), "r"(v) : "memory");
}
__device__ __forceinline__ uint4 ld_rlx_2x64(const void* p) {
    unsigned long long a, b;
    asm volatile("ld.relaxed.gpu.global.v2.b64 {%0,%1}, [%2];" : "=l"(a), "=l"(b) : "l"(p) : "memory");
    return make_uint4((uint32_t)a, (uint32_t)(a >> 32), (uint32_t)b, (uint32_t)(b >> 32));
}
__device__ __forceinline__ void st_rlx_2x64(void* p, const uint4& v) {
    asm volatile("st.relaxed.gpu.global.v2.b64 [%0], {%1,%2};" :: "l"(p),
                 "l"(((unsigned long long)v.y << 32) | v.x), "l"(((unsigned long long)v.w << 32) | v.z) : "memory");
}
__device__ __forceinline__ void st_rlx_64(void* p, uint32_t lo, uint32_t hi) {
    asm volatile("st.relaxed.gpu.global.b64 [%0], %1;" :: "l"(p), "l"(((unsigned long long)hi << 32) | lo) : "memory");
}
__device__ __forceinline__ bool tagged(const uint4& v, uint32_t tag) { return (((v.x ^ tag) | (v.z ^ tag)) & 1u) == 0u; }
__device__ __forceinline__ void sts128(uint32_t a, uint32_t x, uint32_t y, uint32_t z, uint32_t w) {
    asm volatile("st.shared.v4.b32 [%0], {%1,%2,%3,%4};" :: "r"(a), "r"(x), "r"(y), "r"(z), "r"(w) : "memory");
}
template <typename T> __device__ __forceinline__ void pin64(T*& p) { asm volatile("" : "+l"(p)); }
__device__ __forceinline__ void pin32(uint32_t& v) { asm volatile("" : "+r"(v)); }
__device__ __forceinline__ void cbar() { asm volatile("bar.sync 1, 256;" ::: "memory"); }
__device__ __forceinline__ float ex2(float x) { float y; asm("ex2.approx.ftz.f32 %0, %1;" : "=f"(y) : "f"(x)); return y; }

__global__ void __launch_bounds__(NTHREADS, 2)
fused_decode_kernel(const __grid_constant__ Maps maps, const char* __restrict__ wq_raw, __nv_bfloat16* __restrict__ out)
{
    extern __shared__ __align__(1024) char smp[];
    const uint32_t sm = smem_u32(smp);
    const int tid = threadIdx.x, warp = tid >> 5, lane = tid & 31;
    const int cta = blockIdx.x, g = cta >> 4, c = cta & 15, b = c >> 1, half = c & 1;
    const bool ffn = g < 7;
    const uint32_t bar_full = sm + OFF_BAR, bar_empty = bar_full + NCHUNK * 8;
    const uint32_t bar_q = bar_empty + 16 * 8, bar_ml = bar_q + 8, bar_r = bar_q + 16, bar_x = bar_q + 24;

    if (warp == 8) {
        if (lane == 0) {
            mbar_init(bar_x, 1); mbar_init(bar_full, 1); mbar_init(bar_full + 8, 1);
            asm volatile("fence.proxy.async.shared::cta;" ::: "memory");
            mbar_expect(bar_full, CHUNK); tma2d(sm, &maps.wq, cta * 32, 0, bar_full);
            mbar_expect(bar_x, 8192); tma3d(sm + OFF_X, &maps.x, 0, 0, 0, bar_x);
            mbar_expect(bar_full + 8, CHUNK); tma2d(sm + CHUNK, &maps.wq, cta * 32, 256, bar_full + 8);
            if (sm & 1023u) __trap();
            #pragma unroll
            for (int s = 2; s < NCHUNK; s++) mbar_init(bar_full + s * 8, 1);
            #pragma unroll
            for (int s = 0; s < 16; s++) mbar_init(bar_empty + s * 8, (s < 2 || (s >= C_K && s < C_V)) ? 4 : 8);
            mbar_init(bar_q, 1); mbar_init(bar_ml, 1); mbar_init(bar_r, 1);
            mbar_expect(bar_q, 1024); mbar_expect(bar_ml, 32); mbar_expect(bar_r, 4096);
            asm volatile("fence.mbarrier_init.release.cluster;" ::: "memory");
            asm volatile("fence.proxy.async.shared::cta;" ::: "memory");
        }
        __syncwarp();
        asm volatile("barrier.cluster.arrive.relaxed.aligned;" ::: "memory");
        asm volatile("bar.arrive 2, %0;" :: "n"(NTHREADS) : "memory");
        if (lane == 0) {
            if (ffn) {
                mbar_expect(bar_full + 16, CHUNK);
                tma2d(sm + 2 * CHUNK, &maps.w1, cta * 16, 0, bar_full + 16);
                tma2d(sm + 2 * CHUNK + 8192, &maps.w1, cta * 16, 256, bar_full + 16);
            } else mbar_arrive(bar_full + 16);
            const int row0 = (b * 8 + g) * 4096 + 3072 + half * 512;
            uint32_t dst = sm + C_K * CHUNK;
            #pragma unroll 1
            for (int ch = C_K; ch < NCHUNK; ch++) {
                if (ch >= DEPTH) mbar_wait(bar_full + (ch < C_W2 ? ch - DEPTH : ch == C_W2 ? W2_AFTER : WO_AFTER) * 8);
                if (ch >= NSLOT) mbar_wait(bar_empty + (ch - NSLOT) * 8);
                const uint32_t bar = bar_full + ch * 8;
                if (ch < C_W2) {
                    mbar_expect(bar, CHUNK);
                    tma3d(dst, ch < C_V ? &maps.k : &maps.v, 0, row0 + ((ch - C_K) & 7) * 64, 0, bar);
                } else {
                    mbar_expect(bar, ch == C_W2 ? 14336 : CHUNK);
                    tma2d(dst, ch == C_W2 ? &maps.w2 : &maps.wo, g * 64,
                          ch == C_W2 ? c * 112 : c * 256 + (ch - C_WO) * 128, bar);
                }
                dst = (dst == sm + (NSLOT - 1) * CHUNK) ? sm : dst + CHUNK;
            }
        }
        __syncwarp();
        asm volatile("barrier.cluster.wait.aligned;" ::: "memory");
        return;
    }

    if (tid == 0) l2_prefetch(wq_raw + (size_t)cta * 32768, PF_BYTES);
    asm volatile("barrier.cluster.arrive.relaxed.aligned;" ::: "memory");
    const int gl = lane >> 2, t = lane & 3;
    float* lnst = reinterpret_cast<float*>(smp + OFF_STAT + 256);
    volatile uint32_t* epoch_s = reinterpret_cast<volatile uint32_t*>(smp + OFF_STAT + 320);
    const int ru = lane & 7, rp = lane >> 3;
    const int ob = 2 * (ru & 3) + (rp & 1);
    const int ocol = g * 64 + (c >> 2) * 16 + 2 * (c & 3) + (ru >> 2) + 8 * (rp >> 1);
    uint32_t epoch_r = 0;
    if (tid == 64) epoch_r = ld_rlx(&g_epoch);
    asm volatile("bar.sync 2, %0;" :: "n"(NTHREADS) : "memory");
    if (tid == 64) *epoch_s = epoch_r;
    mbar_wait(bar_x);
    uint32_t xf[8];
    #pragma unroll
    for (int j = 0; j < 8; j++)
        xf[j] = *reinterpret_cast<const uint32_t*>(smp + OFF_X + warp * 1024 + gl * 128 + ((j ^ gl) << 4) + t * 4);
    const float resid = __bfloat162float(*reinterpret_cast<const __nv_bfloat16*>(
        smp + OFF_X + g * 1024 + ob * 128 + ((((ocol >> 3) & 7) ^ ob) << 4) + (ocol & 7) * 2));
    {
        const char* xr = smp + OFF_X + (lane >> 3) * 1024 + warp * 128 + (lane & 7) * 16;
        const uint4 xa = *reinterpret_cast<const uint4*>(xr), xb = *reinterpret_cast<const uint4*>(xr + 4096);
        const float sh = bf_lo(*reinterpret_cast<const uint32_t*>(smp + OFF_X + warp * 128));
        const uint32_t w[8] = {xa.x, xa.y, xa.z, xa.w, xb.x, xb.y, xb.z, xb.w};
        float s4[4] = {}, q4[4] = {};
        #pragma unroll
        for (int j = 0; j < 8; j++) {
            const float lo = bf_lo(w[j]) - sh, hi = bf_hi(w[j]) - sh;
            s4[j & 3] += lo + hi;
            q4[j & 3] = fmaf(lo, lo, fmaf(hi, hi, q4[j & 3]));
        }
        float s = (s4[0] + s4[1]) + (s4[2] + s4[3]), q2 = (q4[0] + q4[1]) + (q4[2] + q4[3]);
        #pragma unroll
        for (int o = 16; o > 0; o >>= 1) {
            s += __shfl_xor_sync(0xffffffffu, s, o);
            q2 += __shfl_xor_sync(0xffffffffu, q2, o);
        }
        const float ms = s * (1.f / 512.f), mean = sh + ms;
        q2 = fmaxf(fmaf(-ms, s, q2), 0.f);
        const float den = bf16r(__fsqrt_rn(bf16r(bf16r(q2 * (1.f / 512.f)) + 1e-5f)));
        if (lane == 0) *reinterpret_cast<float2*>(lnst + warp * 2) = make_float2(bf16r(mean), __frcp_rn(den));
    }
    cbar();
    {
        const float2 st = *reinterpret_cast<const float2*>(lnst + gl * 2);
        #pragma unroll
        for (int j = 0; j < 8; j++)
            xf[j] = pack_bf16(bf16r(bf_lo(xf[j]) - st.x) * st.y, bf16r(bf_hi(xf[j]) - st.x) * st.y);
    }
    const uint32_t tag = (*epoch_s + 1u) & 1u;

    float* red = reinterpret_cast<float*>(smp + OFF_RED);
    const int mj = lane >> 3, mr = lane & 7;
    float* r0 = red + (warp * 8 + 2 * t) * RED_PITCH + gl;
    {
        float aq[2][4] = {};
        mbar_wait(bar_full + (warp >> 2) * 8);
        const uint32_t wqs = sm + (warp >> 2) * CHUNK;
        #pragma unroll
        for (int s = 0; s < 4; s++) {
            const int row = (warp & 3) * 64 + s * 16 + (mj >> 1) * 8 + mr;
            #pragma unroll
            for (int j = 0; j < 2; j++) {
                uint32_t a[4];
                ldsm4t(a, wqs + row * 64 + (((2 * j + (mj & 1)) ^ ((row >> 1) & 3)) << 4));
                mma16816(aq[j], a, xf[2 * s], xf[2 * s + 1]);
            }
        }
        __syncwarp();
        if (lane == 0) mbar_arrive(bar_empty + (warp >> 2) * 8);
        #pragma unroll
        for (int j = 0; j < 2; j++) {
            r0[j * 16] = aq[j][0]; r0[RED_PITCH + j * 16] = aq[j][1];
            r0[j * 16 + 8] = aq[j][2]; r0[RED_PITCH + j * 16 + 8] = aq[j][3];
        }
    }
    cbar();
    asm volatile("barrier.cluster.wait.aligned;" ::: "memory");
    if (warp < 4) {
        const int bb = tid >> 4, wd = tid & 15;
        const int col = (wd >> 3) * 16 + ((wd >> 1) & 3) * 2 + (wd & 1) * 8;
        float s0 = 0.f, s1 = 0.f;
        #pragma unroll
        for (int w = 0; w < 8; w++) {
            const float2 f = *reinterpret_cast<const float2*>(red + (w * 8 + bb) * RED_PITCH + col);
            s0 += f.x; s1 += f.y;
        }
        const uint32_t u = pack_bf16(s0, s1);
        const int q0 = (lane & 16) + (lane & 3) * 4;
        const uint32_t u0 = __shfl_sync(0xffffffffu, u, q0), u1 = __shfl_sync(0xffffffffu, u, q0 + 1);
        const uint32_t u2 = __shfl_sync(0xffffffffu, u, q0 + 2), u3 = __shfl_sync(0xffffffffu, u, q0 + 3);
        if (wd < 8) {
            const uint32_t rank = 2 * bb + (wd >> 2);
            st_async4(mapa(sm + OFF_Q + c * 64 + (wd & 3) * 16, rank), u0, u1, u2, u3, mapa(bar_q, rank));
        }
    }
    if (ffn) {
        float ah[4] = {};
        mbar_wait(bar_full + 2 * 8);
        const uint32_t w1s = sm + 2 * CHUNK;
        #pragma unroll
        for (int s = 0; s < 4; s++) {
            const int row = warp * 64 + s * 16 + (mj >> 1) * 8 + mr;
            uint32_t a[4];
            ldsm4t(a, w1s + row * 32 + (((mj & 1) ^ ((row >> 2) & 1)) << 4));
            mma16816(ah, a, xf[2 * s], xf[2 * s + 1]);
        }
        __syncwarp();
        if (lane == 0) mbar_arrive(bar_empty + 2 * 8);
        cbar();
        r0[0] = ah[0]; r0[RED_PITCH] = ah[1]; r0[8] = ah[2]; r0[RED_PITCH + 8] = ah[3];
        cbar();
        if (warp >= 6) {
            const int bb = (tid & 63) >> 3, wd = tid & 7;
            float s0 = 0.f, s1 = 0.f;
            #pragma unroll
            for (int w = 0; w < 8; w++) {
                const float2 f = *reinterpret_cast<const float2*>(red + (w * 8 + bb) * RED_PITCH + 2 * wd);
                s0 += f.x; s1 += f.y;
            }
            s0 = bf16r(s0); s1 = bf16r(s1);
            s0 = __fdividef(s0, 1.f + __expf(-s0)); s1 = __fdividef(s1, 1.f + __expf(-s1));
            const uint32_t u = pack_bf16(s0, s1);
            const uint32_t un = __shfl_down_sync(0xffffffffu, u, 1);
            if (!(wd & 1)) st_rlx_64(g_h + bb * 896 + cta * 8 + wd, (u & ~1u) | tag, un);
        }
    } else {
        __syncwarp();
        if (lane == 0) mbar_arrive(bar_empty + 2 * 8);
    }

    float sc[4][4];
    float m0 = -INFINITY, m1 = -INFINITY;
    {
        mbar_wait_cluster(bar_q);
        uint32_t qb[8][2];
        #pragma unroll
        for (int s = 0; s < 8; s++) {
            const uint2 v = *reinterpret_cast<const uint2*>(smp + OFF_Q + (((gl & 3) * 8 + s) * 4 + t) * 8);
            qb[s][0] = v.x; qb[s][1] = v.y;
        }
        const uint32_t koff = ((warp & 3) * 16 + (mj & 1) * 8 + mr) * 128;
        #pragma unroll
        for (int i = 0; i < 4; i++) {
            const int ck = C_K + 2 * i + (warp >> 2);
            mbar_wait(bar_full + ck * 8);
            const uint32_t ks = sm + (ck % NSLOT) * CHUNK + koff;
            float s0[4] = {}, s1[4] = {};
            #pragma unroll
            for (int s = 0; s < 4; s++) {
                const uint32_t sw = ((2 * s + (mj >> 1)) ^ mr) << 4;
                uint32_t a[4], a2[4];
                ldsm4(a, ks + sw);
                ldsm4(a2, ks + 8192 + sw);
                mma16816(s0, a, qb[s][0], qb[s][1]);
                mma16816(s1, a2, qb[4 + s][0], qb[4 + s][1]);
            }
            __syncwarp();
            if (lane == 0) mbar_arrive(bar_empty + ck * 8);
            #pragma unroll
            for (int k = 0; k < 4; k++) sc[i][k] = bf16r(bf16r(s0[k] + s1[k]) * 0.08838834764831845f);
            m0 = fmaxf(m0, fmaxf(sc[i][0], sc[i][2]));
            m1 = fmaxf(m1, fmaxf(sc[i][1], sc[i][3]));
        }
    }
    float* wmax = reinterpret_cast<float*>(smp + OFF_STAT);
    float* wsum = wmax + 32;
    constexpr float L2E = 1.4426950408889634f;
    {
        #pragma unroll
        for (int o = 4; o < 32; o <<= 1) {
            m0 = fmaxf(m0, __shfl_xor_sync(0xffffffffu, m0, o));
            m1 = fmaxf(m1, __shfl_xor_sync(0xffffffffu, m1, o));
        }
        if (lane < 2) *reinterpret_cast<float2*>(wmax + warp * 4 + 2 * lane) = make_float2(m0, m1);
        cbar();
        #pragma unroll
        for (int w = 0; w < 8; w++) {
            const float2 f = *reinterpret_cast<const float2*>(wmax + w * 4 + 2 * (t & 1));
            m0 = fmaxf(m0, f.x); m1 = fmaxf(m1, f.y);
        }
        float l0 = 0.f, l1 = 0.f;
        uint32_t pw[4][2];
        #pragma unroll
        for (int i = 0; i < 4; i++) {
            const float p0 = ex2((sc[i][0] - m0) * L2E), p1 = ex2((sc[i][1] - m1) * L2E);
            const float p2 = ex2((sc[i][2] - m0) * L2E), p3 = ex2((sc[i][3] - m1) * L2E);
            l0 += p0 + p2; l1 += p1 + p3;
            pw[i][0] = movtrans(pack_bf16(p0, p1));
            pw[i][1] = movtrans(pack_bf16(p2, p3));
        }
        if (lane < 16) {
            char* pd = smp + OFF_P + ((warp >> 2) * 2 + ((warp >> 1) & 1)) * 256 + lane * 16 + (warp & 1) * 8;
            #pragma unroll
            for (int i = 0; i < 4; i++) *reinterpret_cast<uint2*>(pd + i * 1024) = make_uint2(pw[i][0], pw[i][1]);
        }
        #pragma unroll
        for (int o = 4; o < 32; o <<= 1) {
            l0 += __shfl_xor_sync(0xffffffffu, l0, o);
            l1 += __shfl_xor_sync(0xffffffffu, l1, o);
        }
        if (lane < 2) *reinterpret_cast<float2*>(wsum + warp * 4 + 2 * lane) = make_float2(l0, l1);
    }
    cbar();
    float l0 = 0.f, l1 = 0.f;
    #pragma unroll
    for (int w = 0; w < 8; w++) {
        const float2 f = *reinterpret_cast<const float2*>(wsum + w * 4 + 2 * (t & 1));
        l0 += f.x; l1 += f.y;
    }
    if (tid < 2) {
        const uint32_t dst = mapa(sm + OFF_ML + tid * 8, c ^ 1), bar = mapa(bar_ml, c ^ 1);
        st_async2(dst, __float_as_uint(m0), __float_as_uint(m1), bar);
        st_async2(dst + 16, __float_as_uint(l0), __float_as_uint(l1), bar);
    }

    const uint32_t* op = g_o + (((tid >> 4) & 7) * 32 + 2 * c + (tid >> 7)) * 64 + (tid & 15) * 4;
    uint32_t* opub = g_o + ((half * 8 + b) * 32 + g * 4) * 64 + (tid & 63) * 4;
    __nv_bfloat16* outp = out + ob * 512 + ocol;
    uint32_t s_ost = sm + OFF_OST + gl * 256 + (t * 4 + ((warp >> 1) ^ (t & 2))) * 16 + (warp & 1) * 8;
    uint32_t s_rdst = mapa(sm + OFF_RIN + (c * 2 + (warp >> 2)) * 128 + ru * 16, (warp & 3) * 4 + rp);
    uint32_t s_rbar = mapa(bar_r, (warp & 3) * 4 + rp);
    uint32_t s_obw = sm + OFF_OB + (tid >> 4) * 320 + (((tid & 15) ^ ((tid >> 4) & 1)) << 4);
    uint32_t s_obr = sm + OFF_OB + gl * 320 + t * 64 + ((((warp >> 2) * 2) ^ (t & 2) ^ (gl & 1)) << 4);
    const int hb = min(tid / 14, 7), hpc = tid - (tid / 14) * 14;
    const uint32_t* hp = g_h + hb * 896 + c * 56 + hpc * 4;
    uint32_t s_h = sm + OFF_H + hb * 272 + hpc * 16;
    pin64(op); pin64(opub); pin64(outp); pin64(hp);
    uint32_t aoff = sm + (warp >> 2) * 8192 + ((mj >> 1) * 8 + mr) * 128 + (((2 * (warp & 3) + (mj & 1)) ^ mr) << 4);
    uint32_t s_hs = sm + OFF_H + (gl * 68 + (warp >> 2) * 32 + t) * 4;
    uint32_t s_rin = sm + OFF_RIN + lane * 16;
    uint32_t ptid = tid;
    pin32(s_ost); pin32(s_rdst); pin32(s_rbar); pin32(s_obw); pin32(s_obr); pin32(s_h);
    pin32(aoff); pin32(s_hs); pin32(s_rin); pin32(ptid);
    uint4 hv = make_uint4(tag, 0u, tag, 0u);
    if (tid < 112) hv = ld_rlx_2x64(hp);
    if (tid < 64) st_rlx_2x64(opub, make_uint4(tag ^ 1u, 0u, tag ^ 1u, 0u));

    float f0 = 0.f, f1 = 0.f;
    float oc[4][4] = {};
    {
        const int ach = 2 * warp + (mj & 1);
        uint32_t voff = (ach >> 3) * 8192 + ((mj >> 1) * 8 + mr) * 128 + (((ach & 7) ^ mr) << 4);
        pin32(voff);
        const uint4* pfp = reinterpret_cast<const uint4*>(smp + OFF_P) + (lane & 15);
        uint32_t vs = sm + (C_V % NSLOT) * CHUNK;
        #pragma unroll 1
        for (int j = 0; j < 8; j++) {
            const uint4 pa = pfp[j * 32], pb = pfp[j * 32 + 16];
            if (j == 6) {
                for (uint32_t n = 0; !tagged(hv, tag); ) {
                    hv = ld_rlx_2x64(hp);
                    if (++n > POLL_LIMIT) __trap();
                }
                if (tid < 112) sts128(s_h, hv.x, hv.y, hv.z, hv.w);
                __syncwarp();
                mbar_wait_cluster(bar_ml);
                const float* pm = reinterpret_cast<const float*>(smp + OFF_ML) + (t & 1) * 2;
                const float mo0 = pm[0], mo1 = pm[1];
                const float mt0 = fmaxf(m0, mo0), mt1 = fmaxf(m1, mo1);
                const float e0 = ex2((m0 - mt0) * L2E), e1 = ex2((m1 - mt1) * L2E);
                f0 = __fdividef(e0, l0 * e0 + pm[4] * ex2((mo0 - mt0) * L2E));
                f1 = __fdividef(e1, l1 * e1 + pm[5] * ex2((mo1 - mt1) * L2E));
            }
            mbar_wait(bar_full + (C_V + j) * 8);
            uint32_t a[4][4];
            #pragma unroll
            for (int s = 0; s < 4; s++) ldsm4t(a[s], vs + voff + s * 2048);
            mma16816(oc[0], a[0], pa.x, pa.y);
            mma16816(oc[1], a[1], pa.z, pa.w);
            mma16816(oc[2], a[2], pb.x, pb.y);
            mma16816(oc[3], a[3], pb.z, pb.w);
            __syncwarp();
            if (j < 5 && lane == 0) mbar_arrive(bar_empty + (C_V + j) * 8);
            vs = (vs == sm + (NSLOT - 1) * CHUNK) ? sm : vs + CHUNK;
        }
    }
    {
        const float o0 = (oc[0][0] + oc[1][0]) + (oc[2][0] + oc[3][0]);
        const float o1 = (oc[0][1] + oc[1][1]) + (oc[2][1] + oc[3][1]);
        const float o2 = (oc[0][2] + oc[1][2]) + (oc[2][2] + oc[3][2]);
        const float o3 = (oc[0][3] + oc[1][3]) + (oc[2][3] + oc[3][3]);
        const uint32_t u0 = movtrans(pack_bf16(o0 * f0, o1 * f1));
        const uint32_t u1 = movtrans(pack_bf16(o2 * f0, o3 * f1));
        if (!(ptid & 16))
            asm volatile("st.shared.v2.b32 [%0], {%1,%2};" :: "r"(s_ost), "r"((u0 & ~1u) | tag), "r"(u1) : "memory");
        cbar();
        if (ptid < 64) st_rlx_2x64(opub, *reinterpret_cast<const uint4*>(smp + OFF_OST + ptid * 16));
    }

    {
        float ac[4][4] = {};
        mbar_wait(bar_full + C_W2 * 8);
        uint4 oa = ld_rlx_2x64(op), obv = ld_rlx_2x64(op + 16384);
        #pragma unroll
        for (int s = 0; s < 4; s++) {
            if (s < 3 || ptid < 128) {
                uint32_t a[4], h0, h1;
                ldsm4t(a, aoff + (C_W2 % NSLOT) * CHUNK + s * 2048);
                asm volatile("ld.shared.b32 %0, [%1];" : "=r"(h0) : "r"(s_hs + s * 32) : "memory");
                asm volatile("ld.shared.b32 %0, [%1];" : "=r"(h1) : "r"(s_hs + s * 32 + 16) : "memory");
                mma16816(ac[s], a, h0, h1);
            }
        }
        uint32_t wa[8][4];
        bool have0 = false, have1 = false;
        auto wo_part = [&](int i) {
            #pragma unroll
            for (int s = 0; s < 4; s++) ldsm4t(wa[i * 4 + s], aoff + (C_WO % NSLOT + i) * CHUNK + s * 2048);
        };
        for (uint32_t n = 0; ; ) {
            if (!have0 && mbar_test(bar_full + C_WO * 8)) { have0 = true; wo_part(0); }
            if (!have1 && mbar_test(bar_full + (C_WO + 1) * 8)) { have1 = true; wo_part(1); }
            if (++n > POLL_LIMIT) __trap();
            const bool na = !tagged(oa, tag), nb = !tagged(obv, tag);
            if (!__any_sync(0xffffffffu, na || nb)) break;
            if (na) oa = ld_rlx_2x64(op);
            if (nb) obv = ld_rlx_2x64(op + 16384);
        }
        sts128(s_obw, hadd2_bf16(oa.x, obv.x), hadd2_bf16(oa.y, obv.y), hadd2_bf16(oa.z, obv.z), hadd2_bf16(oa.w, obv.w));
        cbar();
        uint4 of[4];
        #pragma unroll
        for (int i = 0; i < 4; i++)
            asm volatile("ld.shared.v4.b32 {%0,%1,%2,%3}, [%4];" : "=r"(of[i].x), "=r"(of[i].y), "=r"(of[i].z), "=r"(of[i].w)
                         : "r"((s_obr ^ ((i & 1) << 4)) + (i >> 1) * 2560) : "memory");
        if (!have0) { mbar_wait(bar_full + C_WO * 8); wo_part(0); }
        mma16816(ac[0], wa[0], of[0].x, of[0].y);
        mma16816(ac[1], wa[1], of[0].z, of[0].w);
        mma16816(ac[2], wa[2], of[1].x, of[1].y);
        mma16816(ac[3], wa[3], of[1].z, of[1].w);
        if (!have1) { mbar_wait(bar_full + (C_WO + 1) * 8); wo_part(1); }
        mma16816(ac[0], wa[4], of[2].x, of[2].y);
        mma16816(ac[1], wa[5], of[2].z, of[2].w);
        mma16816(ac[2], wa[6], of[3].x, of[3].y);
        mma16816(ac[3], wa[7], of[3].z, of[3].w);
        st_async4(s_rdst,
                  __float_as_uint((ac[0][0] + ac[1][0]) + (ac[2][0] + ac[3][0])),
                  __float_as_uint((ac[0][1] + ac[1][1]) + (ac[2][1] + ac[3][1])),
                  __float_as_uint((ac[0][2] + ac[1][2]) + (ac[2][2] + ac[3][2])),
                  __float_as_uint((ac[0][3] + ac[1][3]) + (ac[2][3] + ac[3][3])), s_rbar);
    }

    if (ptid < 32) {
        mbar_wait_cluster(bar_r);
        float4 v[8];
        #pragma unroll
        for (int i = 0; i < 8; i++)
            asm volatile("ld.shared.v4.f32 {%0,%1,%2,%3}, [%4];" : "=f"(v[i].x), "=f"(v[i].y), "=f"(v[i].z), "=f"(v[i].w)
                         : "r"(s_rin + i * 512) : "memory");
        const float s0 = ((v[0].x + v[1].x) + (v[2].x + v[3].x)) + ((v[4].x + v[5].x) + (v[6].x + v[7].x));
        const float s1 = ((v[0].y + v[1].y) + (v[2].y + v[3].y)) + ((v[4].y + v[5].y) + (v[6].y + v[7].y));
        const float s2 = ((v[0].z + v[1].z) + (v[2].z + v[3].z)) + ((v[4].z + v[5].z) + (v[6].z + v[7].z));
        const float s3 = ((v[0].w + v[1].w) + (v[2].w + v[3].w)) + ((v[4].w + v[5].w) + (v[6].w + v[7].w));
        const bool p1 = ptid & 8, p2 = ptid & 16;
        float a = p1 ? s1 : s0, bq = p1 ? s3 : s2;
        a += __shfl_xor_sync(0xffffffffu, p1 ? s0 : s1, 8);
        bq += __shfl_xor_sync(0xffffffffu, p1 ? s2 : s3, 8);
        float r = p2 ? bq : a;
        r += __shfl_xor_sync(0xffffffffu, p2 ? a : bq, 16);
        *outp = __float2bfloat16_rn(r + resid);
        if (cta == 0 && lane == 0) st_rlx(&g_epoch, *epoch_s + 1u);
    }
}

typedef CUresult (*EncodeFn)(CUtensorMap*, CUtensorMapDataType, cuuint32_t, void*, const cuuint64_t*, const cuuint64_t*,
                             const cuuint32_t*, const cuuint32_t*, CUtensorMapInterleave, CUtensorMapSwizzle,
                             CUtensorMapL2promotion, CUtensorMapFloatOOBfill);

void encode(EncodeFn fn, CUtensorMap* m, const void* p, int rank, const cuuint64_t* dims, const cuuint64_t* strides,
            const cuuint32_t* box, CUtensorMapSwizzle sw) {
    const cuuint32_t es[3] = {1, 1, 1};
    fn(m, CU_TENSOR_MAP_DATA_TYPE_BFLOAT16, rank, const_cast<void*>(p), dims, strides, box, es,
       CU_TENSOR_MAP_INTERLEAVE_NONE, sw, CU_TENSOR_MAP_L2_PROMOTION_L2_256B, CU_TENSOR_MAP_FLOAT_OOB_FILL_NONE);
}

}

extern "C" void kernel_launch(void* const* d_in, const int* in_sizes, int n_in, void* d_out, int out_size) {
    (void)in_sizes; (void)n_in; (void)out_size;
    static EncodeFn fn = nullptr;
    if (!fn) {
        cudaDriverEntryPointQueryResult qr;
        cudaGetDriverEntryPoint("cuTensorMapEncodeTiled", (void**)&fn, cudaEnableDefault, &qr);
        cudaFuncSetAttribute(fused_decode_kernel, cudaFuncAttributeMaxDynamicSharedMemorySize, SMEM_BYTES);
        cudaFuncSetAttribute(fused_decode_kernel, cudaFuncAttributeNonPortableClusterSizeAllowed, 1);
    }
    Maps m;
    {
        const cuuint64_t d[3] = {64, 64ull * 4096, 2}, s[2] = {256, 128};
        const cuuint32_t bx[3] = {64, 64, 2};
        encode(fn, &m.k, d_in[1], 3, d, s, bx, CU_TENSOR_MAP_SWIZZLE_128B);
        encode(fn, &m.v, d_in[2], 3, d, s, bx, CU_TENSOR_MAP_SWIZZLE_128B);
    }
    { const cuuint64_t d[3] = {64, 8, 8}, s[2] = {1024, 128}; const cuuint32_t bx[3] = {64, 8, 8};
      encode(fn, &m.x, d_in[0], 3, d, s, bx, CU_TENSOR_MAP_SWIZZLE_128B); }
    { const cuuint64_t d[2] = {4096, 512}, s[1] = {8192}; const cuuint32_t bx[2] = {32, 256};
      encode(fn, &m.wq, d_in[3], 2, d, s, bx, CU_TENSOR_MAP_SWIZZLE_64B); }
    { const cuuint64_t d[2] = {512, 4096}, s[1] = {1024}; const cuuint32_t bx[2] = {64, 128};
      encode(fn, &m.wo, d_in[4], 2, d, s, bx, CU_TENSOR_MAP_SWIZZLE_128B); }
    { const cuuint64_t d[2] = {1792, 512}, s[1] = {3584}; const cuuint32_t bx[2] = {16, 256};
      encode(fn, &m.w1, d_in[6], 2, d, s, bx, CU_TENSOR_MAP_SWIZZLE_32B); }
    { const cuuint64_t d[2] = {512, 1792}, s[1] = {1024}; const cuuint32_t bx[2] = {64, 112};
      encode(fn, &m.w2, d_in[7], 2, d, s, bx, CU_TENSOR_MAP_SWIZZLE_128B); }

    cudaLaunchConfig_t cfg = {};
    cfg.gridDim = dim3(NCTA); cfg.blockDim = dim3(NTHREADS); cfg.dynamicSmemBytes = SMEM_BYTES;
    cfg.stream = cudaStreamPerThread;
    cudaLaunchAttribute at[2];
    at[0].id = cudaLaunchAttributeClusterDimension;
    at[0].val.clusterDim.x = CLUSTER; at[0].val.clusterDim.y = 1; at[0].val.clusterDim.z = 1;
    at[1].id = cudaLaunchAttributeClusterSchedulingPolicyPreference;
    at[1].val.clusterSchedulingPolicyPreference = cudaClusterSchedulingPolicyLoadBalancing;
    cfg.attrs = at; cfg.numAttrs = 2;
    cudaLaunchKernelEx(&cfg, fused_decode_kernel, m, (const char*)d_in[3], (__nv_bfloat16*)d_out);
}
```

```cpp
#include <cuda_runtime.h>
#include <cuda_bf16.h>
#include <cuda.h>
#include <stdint.h>

namespace {

constexpr int NCTA = 128;
constexpr int CLUSTER = 16;
constexpr int NTHREADS = 288;
constexpr int CHUNK = 16384;
constexpr int NSLOT = 6;
constexpr int NCHUNK = 22;
constexpr int C_K = 3, C_V = 11, C_W2 = 19, C_WO = 20;
constexpr int DEPTH = 4;
constexpr int W2_AFTER = 16;
constexpr int WO_AFTER = 18;
constexpr int PF_BYTES = 8192;

constexpr int RED_PITCH = 36;
constexpr int OFF_U = NSLOT * CHUNK;
constexpr int OFF_X = OFF_U;
constexpr int OFF_RED = OFF_U;
constexpr int OFF_P = OFF_U;
constexpr int OFF_OB = OFF_U + 4096;
constexpr int OFF_RIN = OFF_U + 9216;
constexpr int OFF_Q = OFF_RIN + 4096;
constexpr int OFF_OST = OFF_Q;
constexpr int OFF_H = OFF_Q + 1024;
constexpr int OFF_ML = OFF_H + 2176;
constexpr int OFF_STAT = OFF_ML + 32;
constexpr int OFF_BAR = OFF_STAT + 336;
constexpr int SMEM_BYTES = OFF_BAR + 42 * 8;
static_assert(2 * (SMEM_BYTES + 1024) <= 233472, "two CTAs per SM");

struct Maps { CUtensorMap x, wq, k, v, w1, wo, w2; };

__device__ unsigned int g_epoch;
__device__ __align__(128) uint32_t g_o[2 * 8 * 32 * 64];
__device__ __align__(128) uint32_t g_h[8 * 896];

constexpr uint32_t BAR_LIMIT = 1u << 20, POLL_LIMIT = 1u << 23;

__device__ __forceinline__ uint32_t smem_u32(const void* p) { return (uint32_t)__cvta_generic_to_shared(p); }
__device__ __forceinline__ void mbar_init(uint32_t bar, uint32_t cnt) {
    asm volatile("mbarrier.init.shared::cta.b64 [%0], %1;" :: "r"(bar), "r"(cnt) : "memory");
}
__device__ __forceinline__ void mbar_expect(uint32_t bar, uint32_t bytes) {
    asm volatile("mbarrier.arrive.expect_tx.shared::cta.b64 _, [%0], %1;" :: "r"(bar), "r"(bytes) : "memory");
}
__device__ __forceinline__ void mbar_arrive(uint32_t bar) {
    asm volatile("mbarrier.arrive.shared::cta.b64 _, [%0];" :: "r"(bar) : "memory");
}
__device__ __forceinline__ bool mbar_try(uint32_t bar) {
    uint32_t done;
    asm volatile("{\n.reg .pred p;\nmbarrier.try_wait.parity.shared::cta.b64 p, [%1], 0;\nselp.u32 %0, 1, 0, p;\n}"
                 : "=r"(done) : "r"(bar) : "memory");
    return done;
}
__device__ __forceinline__ bool mbar_test(uint32_t bar) {
    uint32_t done;
    asm volatile("{\n.reg .pred p;\nmbarrier.test_wait.parity.shared::cta.b64 p, [%1], 0;\nselp.u32 %0, 1, 0, p;\n}"
                 : "=r"(done) : "r"(bar) : "memory");
    return done;
}
__device__ __forceinline__ void mbar_wait(uint32_t bar) {
    for (uint32_t n = 0; !mbar_try(bar); ) if (++n > BAR_LIMIT) __trap();
}
__device__ __forceinline__ bool mbar_try_cluster(uint32_t bar) {
    uint32_t done;
    asm volatile("{\n.reg .pred p;\nmbarrier.try_wait.parity.acquire.cluster.shared::cta.b64 p, [%1], 0;\nselp.u32 %0, 1, 0, p;\n}"
                 : "=r"(done) : "r"(bar) : "memory");
    return done;
}
__device__ __forceinline__ void mbar_wait_cluster(uint32_t bar) {
    for (uint32_t n = 0; !mbar_try_cluster(bar); ) if (++n > BAR_LIMIT) __trap();
}
__device__ __forceinline__ uint32_t mapa(uint32_t addr, uint32_t rank) {
    uint32_t r; asm("mapa.shared::cluster.u32 %0, %1, %2;" : "=r"(r) : "r"(addr), "r"(rank)); return r;
}
__device__ __forceinline__ void st_async2(uint32_t dst, uint32_t a, uint32_t b, uint32_t bar) {
    asm volatile("st.async.weak.shared::cluster.mbarrier::complete_tx::bytes.v2.b32 [%0], {%1,%2}, [%3];"
                 :: "r"(dst), "r"(a), "r"(b), "r"(bar) : "memory");
}
__device__ __forceinline__ void st_async4(uint32_t dst, uint32_t a, uint32_t b, uint32_t c, uint32_t d, uint32_t bar) {
    asm volatile("st.async.weak.shared::cluster.mbarrier::complete_tx::bytes.v4.b32 [%0], {%1,%2,%3,%4}, [%5];"
                 :: "r"(dst), "r"(a), "r"(b), "r"(c), "r"(d), "r"(bar) : "memory");
}
__device__ __forceinline__ void tma2d(uint32_t dst, const CUtensorMap* m, int c0, int c1, uint32_t bar) {
    asm volatile("cp.async.bulk.tensor.2d.shared::cluster.global.mbarrier::complete_tx::bytes [%0], [%1, {%3, %4}], [%2];"
                 :: "r"(dst), "l"(m), "r"(bar), "r"(c0), "r"(c1) : "memory");
}
__device__ __forceinline__ void tma3d(uint32_t dst, const CUtensorMap* m, int c0, int c1, int c2, uint32_t bar) {
    asm volatile("cp.async.bulk.tensor.3d.shared::cluster.global.mbarrier::complete_tx::bytes [%0], [%1, {%3, %4, %5}], [%2];"
                 :: "r"(dst), "l"(m), "r"(bar), "r"(c0), "r"(c1), "r"(c2) : "memory");
}
__device__ __forceinline__ void l2_prefetch(const void* src, uint32_t bytes) {
    asm volatile("cp.async.bulk.prefetch.L2.global [%0], %1;" :: "l"(src), "r"(bytes) : "memory");
}
__device__ __forceinline__ void ldsm4(uint32_t (&r)[4], uint32_t addr) {
    asm volatile("ldmatrix.sync.aligned.m8n8.x4.shared.b16 {%0,%1,%2,%3}, [%4];"
                 : "=r"(r[0]), "=r"(r[1]), "=r"(r[2]), "=r"(r[3]) : "r"(addr) : "memory");
}
__device__ __forceinline__ void ldsm4t(uint32_t (&r)[4], uint32_t addr) {
    asm volatile("ldmatrix.sync.aligned.m8n8.x4.trans.shared.b16 {%0,%1,%2,%3}, [%4];"
                 : "=r"(r[0]), "=r"(r[1]), "=r"(r[2]), "=r"(r[3]) : "r"(addr) : "memory");
}
__device__ __forceinline__ void mma16816(float (&d)[4], const uint32_t (&a)[4], uint32_t b0, uint32_t b1) {
    asm volatile("mma.sync.aligned.m16n8k16.row.col.f32.bf16.bf16.f32 {%0,%1,%2,%3}, {%4,%5,%6,%7}, {%8,%9}, {%0,%1,%2,%3};"
                 : "+f"(d[0]), "+f"(d[1]), "+f"(d[2]), "+f"(d[3])
                 : "r"(a[0]), "r"(a[1]), "r"(a[2]), "r"(a[3]), "r"(b0), "r"(b1));
}
__device__ __forceinline__ uint32_t movtrans(uint32_t a) {
    uint32_t d;
    asm volatile("movmatrix.sync.aligned.m8n8.trans.b16 %0, %1;" : "=r"(d) : "r"(a));
    return d;
}
__device__ __forceinline__ uint32_t pack_bf16(float lo, float hi) {
    uint32_t d;
    asm("cvt.rn.bf16x2.f32 %0, %1, %2;" : "=r"(d) : "f"(hi), "f"(lo));
    return d;
}
__device__ __forceinline__ float bf16r(float x) { return __bfloat162float(__float2bfloat16_rn(x)); }
__device__ __forceinline__ float bf_lo(uint32_t u) { return __uint_as_float(u << 16); }
__device__ __forceinline__ float bf_hi(uint32_t u) { return __uint_as_float(u & 0xffff0000u); }
__device__ __forceinline__ uint32_t hadd2_bf16(uint32_t a, uint32_t b) {
    uint32_t d;
    asm("add.rn.bf16x2 %0, %1, %2;" : "=r"(d) : "r"(a), "r"(b));
    return d;
}
__device__ __forceinline__ uint32_t ld_rlx(const uint32_t* p) {
    uint32_t v; asm volatile("ld.relaxed.gpu.global.u32 %0, [%1];" : "=r"(v) : "l"(p) : "memory"); return v;
}
__device__ __forceinline__ void st_rlx(uint32_t* p, uint32_t v) {
    asm volatile("st.relaxed.gpu.global.u32 [%0], %1;" :: "l"(p), "r"(v) : "memory");
}
__device__ __forceinline__ uint4 ld_rlx_2x64(const void* p) {
    unsigned long long a, b;
    asm volatile("ld.relaxed.gpu.global.v2.b64 {%0,%1}, [%2];" : "=l"(a), "=l"(b) : "l"(p) : "memory");
    return make_uint4((uint32_t)a, (uint32_t)(a >> 32), (uint32_t)b, (uint32_t)(b >> 32));
}
__device__ __forceinline__ void st_rlx_2x64(void* p, const uint4& v) {
    asm volatile("st.relaxed.gpu.global.v2.b64 [%0], {%1,%2};" :: "l"(p),
                 "l"(((unsigned long long)v.y << 32) | v.x), "l"(((unsigned long long)v.w << 32) | v.z) : "memory");
}
__device__ __forceinline__ void st_rlx_64(void* p, uint32_t lo, uint32_t hi) {
    asm volatile("st.relaxed.gpu.global.b64 [%0], %1;" :: "l"(p), "l"(((unsigned long long)hi << 32) | lo) : "memory");
}
__device__ __forceinline__ bool tagged(const uint4& v, uint32_t tag) { return (((v.x ^ tag) | (v.z ^ tag)) & 1u) == 0u; }
__device__ __forceinline__ void sts128(uint32_t a, uint32_t x, uint32_t y, uint32_t z, uint32_t w) {
    asm volatile("st.shared.v4.b32 [%0], {%1,%2,%3,%4};" :: "r"(a), "r"(x), "r"(y), "r"(z), "r"(w) : "memory");
}
template <typename T> __device__ __forceinline__ void pin64(T*& p) { asm volatile("" : "+l"(p)); }
__device__ __forceinline__ void pin32(uint32_t& v) { asm volatile("" : "+r"(v)); }
__device__ __forceinline__ void cbar() { asm volatile("bar.sync 1, 256;" ::: "memory"); }
__device__ __forceinline__ float ex2(float x) { float y; asm("ex2.approx.ftz.f32 %0, %1;" : "=f"(y) : "f"(x)); return y; }

__global__ void __launch_bounds__(NTHREADS, 2)
fused_decode_kernel(const __grid_constant__ Maps maps, const char* __restrict__ wq_raw, __nv_bfloat16* __restrict__ out)
{
    extern __shared__ __align__(1024) char smp[];
    const uint32_t sm = smem_u32(smp);
    const int tid = threadIdx.x, warp = tid >> 5, lane = tid & 31;
    const int cta = blockIdx.x, g = cta >> 4, c = cta & 15, b = c >> 1, half = c & 1;
    const bool ffn = g < 7;
    const uint32_t bar_full = sm + OFF_BAR, bar_empty = bar_full + NCHUNK * 8;
    const uint32_t bar_q = bar_empty + 16 * 8, bar_ml = bar_q + 8, bar_r = bar_q + 16, bar_x = bar_q + 24;

    if (warp == 8) {
        if (lane == 0) {
            mbar_init(bar_x, 1); mbar_init(bar_full, 1); mbar_init(bar_full + 8, 1);
            asm volatile("fence.proxy.async.shared::cta;" ::: "memory");
            mbar_expect(bar_full, CHUNK); tma2d(sm, &maps.wq, cta * 32, 0, bar_full);
            mbar_expect(bar_x, 8192); tma3d(sm + OFF_X, &maps.x, 0, 0, 0, bar_x);
            mbar_expect(bar_full + 8, CHUNK); tma2d(sm + CHUNK, &maps.wq, cta * 32, 256, bar_full + 8);
            if (sm & 1023u) __trap();
            #pragma unroll
            for (int s = 2; s < NCHUNK; s++) mbar_init(bar_full + s * 8, 1);
            #pragma unroll
            for (int s = 0; s < 16; s++) mbar_init(bar_empty + s * 8, (s < 2 || (s >= C_K && s < C_V)) ? 4 : 8);
            mbar_init(bar_q, 1); mbar_init(bar_ml, 1); mbar_init(bar_r, 1);
            mbar_expect(bar_q, 1024); mbar_expect(bar_ml, 32); mbar_expect(bar_r, 4096);
            asm volatile("fence.mbarrier_init.release.cluster;" ::: "memory");
            asm volatile("fence.proxy.async.shared::cta;" ::: "memory");
        }
        __syncwarp();
        asm volatile("barrier.cluster.arrive.relaxed.aligned;" ::: "memory");
        asm volatile("bar.arrive 2, %0;" :: "n"(NTHREADS) : "memory");
        if (lane == 0) {
            if (ffn) {
                mbar_expect(bar_full + 16, CHUNK);
                tma2d(sm + 2 * CHUNK, &maps.w1, cta * 16, 0, bar_full + 16);
                tma2d(sm + 2 * CHUNK + 8192, &maps.w1, cta * 16, 256, bar_full + 16);
            } else mbar_arrive(bar_full + 16);
            const int row0 = (b * 8 + g) * 4096 + 3072 + half * 512;
            uint32_t dst = sm + C_K * CHUNK;
            #pragma unroll 1
            for (int ch = C_K; ch < NCHUNK; ch++) {
                if (ch >= DEPTH) mbar_wait(bar_full + (ch < C_W2 ? ch - DEPTH : ch == C_W2 ? W2_AFTER : WO_AFTER) * 8);
                if (ch >= NSLOT) mbar_wait(bar_empty + (ch - NSLOT) * 8);
                const uint32_t bar = bar_full + ch * 8;
                if (ch < C_W2) {
                    mbar_expect(bar, CHUNK);
                    tma3d(dst, ch < C_V ? &maps.k : &maps.v, 0, row0 + ((ch - C_K) & 7) * 64, 0, bar);
                } else {
                    mbar_expect(bar, ch == C_W2 ? 14336 : CHUNK);
                    tma2d(dst, ch == C_W2 ? &maps.w2 : &maps.wo, g * 64,
                          ch == C_W2 ? c * 112 : c * 256 + (ch - C_WO) * 128, bar);
                }
                dst = (dst == sm + (NSLOT - 1) * CHUNK) ? sm : dst + CHUNK;
            }
        }
        __syncwarp();
        asm volatile("barrier.cluster.wait.aligned;" ::: "memory");
        return;
    }

    if (tid == 0) l2_prefetch(wq_raw + (size_t)cta * 32768, PF_BYTES);
    asm volatile("barrier.cluster.arrive.relaxed.aligned;" ::: "memory");
    const int gl = lane >> 2, t = lane & 3;
    float* lnst = reinterpret_cast<float*>(smp + OFF_STAT + 256);
    volatile uint32_t* epoch_s = reinterpret_cast<volatile uint32_t*>(smp + OFF_STAT + 320);
    const int ru = lane & 7, rp = lane >> 3;
    const int ob = 2 * (ru & 3) + (rp & 1);
    const int ocol = g * 64 + (c >> 2) * 16 + 2 * (c & 3) + (ru >> 2) + 8 * (rp >> 1);
    uint32_t epoch_r = 0;
    if (tid == 64) epoch_r = ld_rlx(&g_epoch);
    asm volatile("bar.sync 2, %0;" :: "n"(NTHREADS) : "memory");
    if (tid == 64) *epoch_s = epoch_r;
    mbar_wait(bar_x);
    uint32_t xf[8];
    #pragma unroll
    for (int j = 0; j < 8; j++)
        xf[j] = *reinterpret_cast<const uint32_t*>(smp + OFF_X + warp * 1024 + gl * 128 + ((j ^ gl) << 4) + t * 4);
    const float resid = __bfloat162float(*reinterpret_cast<const __nv_bfloat16*>(
        smp + OFF_X + g * 1024 + ob * 128 + ((((ocol >> 3) & 7) ^ ob) << 4) + (ocol & 7) * 2));
    {
        const char* xr = smp + OFF_X + (lane >> 3) * 1024 + warp * 128 + (lane & 7) * 16;
        const uint4 xa = *reinterpret_cast<const uint4*>(xr), xb = *reinterpret_cast<const uint4*>(xr + 4096);
        const float sh = bf_lo(*reinterpret_cast<const uint32_t*>(smp + OFF_X + warp * 128));
        const uint32_t w[8] = {xa.x, xa.y, xa.z, xa.w, xb.x, xb.y, xb.z, xb.w};
        float s4[4] = {}, q4[4] = {};
        #pragma unroll
        for (int j = 0; j < 8; j++) {
            const float lo = bf_lo(w[j]) - sh, hi = bf_hi(w[j]) - sh;
            s4[j & 3] += lo + hi;
            q4[j & 3] = fmaf(lo, lo, fmaf(hi, hi, q4[j & 3]));
        }
        float s = (s4[0] + s4[1]) + (s4[2] + s4[3]), q2 = (q4[0] + q4[1]) + (q4[2] + q4[3]);
        #pragma unroll
        for (int o = 16; o > 0; o >>= 1) {
            s += __shfl_xor_sync(0xffffffffu, s, o);
            q2 += __shfl_xor_sync(0xffffffffu, q2, o);
        }
        const float ms = s * (1.f / 512.f), mean = sh + ms;
        q2 = fmaxf(fmaf(-ms, s, q2), 0.f);
        const float den = bf16r(__fsqrt_rn(bf16r(bf16r(q2 * (1.f / 512.f)) + 1e-5f)));
        if (lane == 0) *reinterpret_cast<float2*>(lnst + warp * 2) = make_float2(bf16r(mean), __frcp_rn(den));
    }
    cbar();
    {
        const float2 st = *reinterpret_cast<const float2*>(lnst + gl * 2);
        #pragma unroll
        for (int j = 0; j < 8; j++)
            xf[j] = pack_bf16(bf16r(bf_lo(xf[j]) - st.x) * st.y, bf16r(bf_hi(xf[j]) - st.x) * st.y);
    }
    const uint32_t tag = (*epoch_s + 1u) & 1u;

    float* red = reinterpret_cast<float*>(smp + OFF_RED);
    const int mj = lane >> 3, mr = lane & 7;
    float* r0 = red + (warp * 8 + 2 * t) * RED_PITCH + gl;
    {
        float aq[2][4] = {};
        mbar_wait(bar_full + (warp >> 2) * 8);
        const uint32_t wqs = sm + (warp >> 2) * CHUNK;
        #pragma unroll
        for (int s = 0; s < 4; s++) {
            const int row = (warp & 3) * 64 + s * 16 + (mj >> 1) * 8 + mr;
            #pragma unroll
            for (int j = 0; j < 2; j++) {
                uint32_t a[4];
                ldsm4t(a, wqs + row * 64 + (((2 * j + (mj & 1)) ^ ((row >> 1) & 3)) << 4));
                mma16816(aq[j], a, xf[2 * s], xf[2 * s + 1]);
            }
        }
        __syncwarp();
        if (lane == 0) mbar_arrive(bar_empty + (warp >> 2) * 8);
        #pragma unroll
        for (int j = 0; j < 2; j++) {
            r0[j * 16] = aq[j][0]; r0[RED_PITCH + j * 16] = aq[j][1];
            r0[j * 16 + 8] = aq[j][2]; r0[RED_PITCH + j * 16 + 8] = aq[j][3];
        }
    }
    cbar();
    asm volatile("barrier.cluster.wait.aligned;" ::: "memory");
    if (warp < 4) {
        const int bb = tid >> 4, wd = tid & 15;
        const int col = (wd >> 3) * 16 + ((wd >> 1) & 3) * 2 + (wd & 1) * 8;
        float s0 = 0.f, s1 = 0.f;
        #pragma unroll
        for (int w = 0; w < 8; w++) {
            const float2 f = *reinterpret_cast<const float2*>(red + (w * 8 + bb) * RED_PITCH + col);
            s0 += f.x; s1 += f.y;
        }
        const uint32_t u = pack_bf16(s0, s1);
        const int q0 = (lane & 16) + (lane & 3) * 4;
        const uint32_t u0 = __shfl_sync(0xffffffffu, u, q0), u1 = __shfl_sync(0xffffffffu, u, q0 + 1);
        const uint32_t u2 = __shfl_sync(0xffffffffu, u, q0 + 2), u3 = __shfl_sync(0xffffffffu, u, q0 + 3);
        if (wd < 8) {
            const uint32_t rank = 2 * bb + (wd >> 2);
            st_async4(mapa(sm + OFF_Q + c * 64 + (wd & 3) * 16, rank), u0, u1, u2, u3, mapa(bar_q, rank));
        }
    }
    if (ffn) {
        float ah[4] = {};
        mbar_wait(bar_full + 2 * 8);
        const uint32_t w1s = sm + 2 * CHUNK;
        #pragma unroll
        for (int s = 0; s < 4; s++) {
            const int row = warp * 64 + s * 16 + (mj >> 1) * 8 + mr;
            uint32_t a[4];
            ldsm4t(a, w1s + row * 32 + (((mj & 1) ^ ((row >> 2) & 1)) << 4));
            mma16816(ah, a, xf[2 * s], xf[2 * s + 1]);
        }
        __syncwarp();
        if (lane == 0) mbar_arrive(bar_empty + 2 * 8);
        cbar();
        r0[0] = ah[0]; r0[RED_PITCH] = ah[1]; r0[8] = ah[2]; r0[RED_PITCH + 8] = ah[3];
        cbar();
        if (warp >= 6) {
            const int bb = (tid & 63) >> 3, wd = tid & 7;
            float s0 = 0.f, s1 = 0.f;
            #pragma unroll
            for (int w = 0; w < 8; w++) {
                const float2 f = *reinterpret_cast<const float2*>(red + (w * 8 + bb) * RED_PITCH + 2 * wd);
                s0 += f.x; s1 += f.y;
            }
            s0 = bf16r(s0); s1 = bf16r(s1);
            s0 = __fdividef(s0, 1.f + __expf(-s0)); s1 = __fdividef(s1, 1.f + __expf(-s1));
            const uint32_t u = pack_bf16(s0, s1);
            const uint32_t un = __shfl_down_sync(0xffffffffu, u, 1);
            if (!(wd & 1)) st_rlx_64(g_h + bb * 896 + cta * 8 + wd, (u & ~1u) | tag, un);
        }
    } else {
        __syncwarp();
        if (lane == 0) mbar_arrive(bar_empty + 2 * 8);
    }

    float sc[4][4];
    float m0 = -INFINITY, m1 = -INFINITY;
    {
        mbar_wait_cluster(bar_q);
        uint32_t qb[8][2];
        #pragma unroll
        for (int s = 0; s < 8; s++) {
            const uint2 v = *reinterpret_cast<const uint2*>(smp + OFF_Q + (((gl & 3) * 8 + s) * 4 + t) * 8);
            qb[s][0] = v.x; qb[s][1] = v.y;
        }
        const uint32_t koff = ((warp & 3) * 16 + (mj & 1) * 8 + mr) * 128;
        #pragma unroll
        for (int i = 0; i < 4; i++) {
            const int ck = C_K + 2 * i + (warp >> 2);
            mbar_wait(bar_full + ck * 8);
            const uint32_t ks = sm + (ck % NSLOT) * CHUNK + koff;
            float s0[4] = {}, s1[4] = {};
            #pragma unroll
            for (int s = 0; s < 4; s++) {
                const uint32_t sw = ((2 * s + (mj >> 1)) ^ mr) << 4;
                uint32_t a[4], a2[4];
                ldsm4(a, ks + sw);
                ldsm4(a2, ks + 8192 + sw);
                mma16816(s0, a, qb[s][0], qb[s][1]);
                mma16816(s1, a2, qb[4 + s][0], qb[4 + s][1]);
            }
            __syncwarp();
            if (lane == 0) mbar_arrive(bar_empty + ck * 8);
            #pragma unroll
            for (int k = 0; k < 4; k++) sc[i][k] = bf16r(bf16r(s0[k] + s1[k]) * 0.08838834764831845f);
            m0 = fmaxf(m0, fmaxf(sc[i][0], sc[i][2]));
            m1 = fmaxf(m1, fmaxf(sc[i][1], sc[i][3]));
        }
    }
    float* wmax = reinterpret_cast<float*>(smp + OFF_STAT);
    float* wsum = wmax + 32;
    constexpr float L2E = 1.4426950408889634f;
    {
        #pragma unroll
        for (int o = 4; o < 32; o <<= 1) {
            m0 = fmaxf(m0, __shfl_xor_sync(0xffffffffu, m0, o));
            m1 = fmaxf(m1, __shfl_xor_sync(0xffffffffu, m1, o));
        }
        if (lane < 2) *reinterpret_cast<float2*>(wmax + warp * 4 + 2 * lane) = make_float2(m0, m1);
        cbar();
        #pragma unroll
        for (int w = 0; w < 8; w++) {
            const float2 f = *reinterpret_cast<const float2*>(wmax + w * 4 + 2 * (t & 1));
            m0 = fmaxf(m0, f.x); m1 = fmaxf(m1, f.y);
        }
        float l0 = 0.f, l1 = 0.f;
        uint32_t pw[4][2];
        #pragma unroll
        for (int i = 0; i < 4; i++) {
            const float p0 = ex2((sc[i][0] - m0) * L2E), p1 = ex2((sc[i][1] - m1) * L2E);
            const float p2 = ex2((sc[i][2] - m0) * L2E), p3 = ex2((sc[i][3] - m1) * L2E);
            l0 += p0 + p2; l1 += p1 + p3;
            pw[i][0] = movtrans(pack_bf16(p0, p1));
            pw[i][1] = movtrans(pack_bf16(p2, p3));
        }
        if (lane < 16) {
            char* pd = smp + OFF_P + ((warp >> 2) * 2 + ((warp >> 1) & 1)) * 256 + lane * 16 + (warp & 1) * 8;
            #pragma unroll
            for (int i = 0; i < 4; i++) *reinterpret_cast<uint2*>(pd + i * 1024) = make_uint2(pw[i][0], pw[i][1]);
        }
        #pragma unroll
        for (int o = 4; o < 32; o <<= 1) {
            l0 += __shfl_xor_sync(0xffffffffu, l0, o);
            l1 += __shfl_xor_sync(0xffffffffu, l1, o);
        }
        if (lane < 2) *reinterpret_cast<float2*>(wsum + warp * 4 + 2 * lane) = make_float2(l0, l1);
    }
    cbar();
    float l0 = 0.f, l1 = 0.f;
    #pragma unroll
    for (int w = 0; w < 8; w++) {
        const float2 f = *reinterpret_cast<const float2*>(wsum + w * 4 + 2 * (t & 1));
        l0 += f.x; l1 += f.y;
    }
    if (tid < 2) {
        const uint32_t dst = mapa(sm + OFF_ML + tid * 8, c ^ 1), bar = mapa(bar_ml, c ^ 1);
        st_async2(dst, __float_as_uint(m0), __float_as_uint(m1), bar);
        st_async2(dst + 16, __float_as_uint(l0), __float_as_uint(l1), bar);
    }

    const uint32_t* op = g_o + (((tid >> 4) & 7) * 32 + 2 * c + (tid >> 7)) * 64 + (tid & 15) * 4;
    uint32_t* opub = g_o + ((half * 8 + b) * 32 + g * 4) * 64 + (tid & 63) * 4;
    __nv_bfloat16* outp = out + ob * 512 + ocol;
    uint32_t s_ost = sm + OFF_OST + gl * 256 + (t * 4 + ((warp >> 1) ^ (t & 2))) * 16 + (warp & 1) * 8;
    uint32_t s_rdst = mapa(sm + OFF_RIN + (c * 2 + (warp >> 2)) * 128 + ru * 16, (warp & 3) * 4 + rp);
    uint32_t s_rbar = mapa(bar_r, (warp & 3) * 4 + rp);
    uint32_t s_obw = sm + OFF_OB + (tid >> 4) * 320 + (((tid & 15) ^ ((tid >> 4) & 1)) << 4);
    uint32_t s_obr = sm + OFF_OB + gl * 320 + t * 64 + ((((warp >> 2) * 2) ^ (t & 2) ^ (gl & 1)) << 4);
    const int hb = min(tid / 14, 7), hpc = tid - (tid / 14) * 14;
    const uint32_t* hp = g_h + hb * 896 + c * 56 + hpc * 4;
    uint32_t s_h = sm + OFF_H + hb * 272 + hpc * 16;
    pin64(op); pin64(opub); pin64(outp); pin64(hp);
    uint32_t aoff = sm + (warp >> 2) * 8192 + ((mj >> 1) * 8 + mr) * 128 + (((2 * (warp & 3) + (mj & 1)) ^ mr) << 4);
    uint32_t s_hs = sm + OFF_H + (gl * 68 + (warp >> 2) * 32 + t) * 4;
    uint32_t s_rin = sm + OFF_RIN + lane * 16;
    uint32_t ptid = tid;
    pin32(s_ost); pin32(s_rdst); pin32(s_rbar); pin32(s_obw); pin32(s_obr); pin32(s_h);
    pin32(aoff); pin32(s_hs); pin32(s_rin); pin32(ptid);
    uint4 hv = make_uint4(tag, 0u, tag, 0u);
    if (tid < 112) hv = ld_rlx_2x64(hp);
    if (tid < 64) st_rlx_2x64(opub, make_uint4(tag ^ 1u, 0u, tag ^ 1u, 0u));

    float f0 = 0.f, f1 = 0.f;
    float oc[4][4] = {};
    {
        const int ach = 2 * warp + (mj & 1);
        uint32_t voff = (ach >> 3) * 8192 + ((mj >> 1) * 8 + mr) * 128 + (((ach & 7) ^ mr) << 4);
        pin32(voff);
        const uint4* pfp = reinterpret_cast<const uint4*>(smp + OFF_P) + (lane & 15);
        uint32_t vs = sm + (C_V % NSLOT) * CHUNK;
        #pragma unroll 1
        for (int j = 0; j < 8; j++) {
            const uint4 pa = pfp[j * 32], pb = pfp[j * 32 + 16];
            if (j == 6) {
                for (uint32_t n = 0; !tagged(hv, tag); ) {
                    hv = ld_rlx_2x64(hp);
                    if (++n > POLL_LIMIT) __trap();
                }
                if (tid < 112) sts128(s_h, hv.x, hv.y, hv.z, hv.w);
                __syncwarp();
                mbar_wait_cluster(bar_ml);
                const float* pm = reinterpret_cast<const float*>(smp + OFF_ML) + (t & 1) * 2;
                const float mo0 = pm[0], mo1 = pm[1];
                const float mt0 = fmaxf(m0, mo0), mt1 = fmaxf(m1, mo1);
                const float e0 = ex2((m0 - mt0) * L2E), e1 = ex2((m1 - mt1) * L2E);
                f0 = __fdividef(e0, l0 * e0 + pm[4] * ex2((mo0 - mt0) * L2E));
                f1 = __fdividef(e1, l1 * e1 + pm[5] * ex2((mo1 - mt1) * L2E));
            }
            mbar_wait(bar_full + (C_V + j) * 8);
            uint32_t a[4][4];
            #pragma unroll
            for (int s = 0; s < 4; s++) ldsm4t(a[s], vs + voff + s * 2048);
            mma16816(oc[0], a[0], pa.x, pa.y);
            mma16816(oc[1], a[1], pa.z, pa.w);
            mma16816(oc[2], a[2], pb.x, pb.y);
            mma16816(oc[3], a[3], pb.z, pb.w);
            __syncwarp();
            if (j < 5 && lane == 0) mbar_arrive(bar_empty + (C_V + j) * 8);
            vs = (vs == sm + (NSLOT - 1) * CHUNK) ? sm : vs + CHUNK;
        }
    }
    {
        const float o0 = (oc[0][0] + oc[1][0]) + (oc[2][0] + oc[3][0]);
        const float o1 = (oc[0][1] + oc[1][1]) + (oc[2][1] + oc[3][1]);
        const float o2 = (oc[0][2] + oc[1][2]) + (oc[2][2] + oc[3][2]);
        const float o3 = (oc[0][3] + oc[1][3]) + (oc[2][3] + oc[3][3]);
        const uint32_t u0 = movtrans(pack_bf16(o0 * f0, o1 * f1));
        const uint32_t u1 = movtrans(pack_bf16(o2 * f0, o3 * f1));
        if (!(ptid & 16))
            asm volatile("st.shared.v2.b32 [%0], {%1,%2};" :: "r"(s_ost), "r"((u0 & ~1u) | tag), "r"(u1) : "memory");
        cbar();
        if (ptid < 64) st_rlx_2x64(opub, *reinterpret_cast<const uint4*>(smp + OFF_OST + ptid * 16));
    }

    {
        float ac[4][4] = {};
        mbar_wait(bar_full + C_W2 * 8);
        uint4 oa = ld_rlx_2x64(op), obv = ld_rlx_2x64(op + 16384);
        #pragma unroll
        for (int s = 0; s < 4; s++) {
            if (s < 3 || ptid < 128) {
                uint32_t a[4], h0, h1;
                ldsm4t(a, aoff + (C_W2 % NSLOT) * CHUNK + s * 2048);
                asm volatile("ld.shared.b32 %0, [%1];" : "=r"(h0) : "r"(s_hs + s * 32) : "memory");
                asm volatile("ld.shared.b32 %0, [%1];" : "=r"(h1) : "r"(s_hs + s * 32 + 16) : "memory");
                mma16816(ac[s], a, h0, h1);
            }
        }
        uint32_t wa[8][4];
        bool have0 = false, have1 = false;
        auto wo_part = [&](int i) {
            #pragma unroll
            for (int s = 0; s < 4; s++) ldsm4t(wa[i * 4 + s], aoff + (C_WO % NSLOT + i) * CHUNK + s * 2048);
        };
        for (uint32_t n = 0; ; ) {
            if (!have0 && __all_sync(0xffffffffu, mbar_test(bar_full + C_WO * 8))) { have0 = true; wo_part(0); }
            if (!have1 && __all_sync(0xffffffffu, mbar_test(bar_full + (C_WO + 1) * 8))) { have1 = true; wo_part(1); }
            if (++n > POLL_LIMIT) __trap();
            const bool na = !tagged(oa, tag), nb = !tagged(obv, tag);
            if (!__any_sync(0xffffffffu, na || nb)) break;
            if (na) oa = ld_rlx_2x64(op);
            if (nb) obv = ld_rlx_2x64(op + 16384);
        }
        sts128(s_obw, hadd2_bf16(oa.x, obv.x), hadd2_bf16(oa.y, obv.y), hadd2_bf16(oa.z, obv.z), hadd2_bf16(oa.w, obv.w));
        cbar();
        uint4 of[4];
        #pragma unroll
        for (int i = 0; i < 4; i++)
            asm volatile("ld.shared.v4.b32 {%0,%1,%2,%3}, [%4];" : "=r"(of[i].x), "=r"(of[i].y), "=r"(of[i].z), "=r"(of[i].w)
                         : "r"((s_obr ^ ((i & 1) << 4)) + (i >> 1) * 2560) : "memory");
        if (!have0) { mbar_wait(bar_full + C_WO * 8); wo_part(0); }
        mma16816(ac[0], wa[0], of[0].x, of[0].y);
        mma16816(ac[1], wa[1], of[0].z, of[0].w);
        mma16816(ac[2], wa[2], of[1].x, of[1].y);
        mma16816(ac[3], wa[3], of[1].z, of[1].w);
        if (!have1) { mbar_wait(bar_full + (C_WO + 1) * 8); wo_part(1); }
        mma16816(ac[0], wa[4], of[2].x, of[2].y);
        mma16816(ac[1], wa[5], of[2].z, of[2].w);
        mma16816(ac[2], wa[6], of[3].x, of[3].y);
        mma16816(ac[3], wa[7], of[3].z, of[3].w);
        st_async4(s_rdst,
                  __float_as_uint((ac[0][0] + ac[1][0]) + (ac[2][0] + ac[3][0])),
                  __float_as_uint((ac[0][1] + ac[1][1]) + (ac[2][1] + ac[3][1])),
                  __float_as_uint((ac[0][2] + ac[1][2]) + (ac[2][2] + ac[3][2])),
                  __float_as_uint((ac[0][3] + ac[1][3]) + (ac[2][3] + ac[3][3])), s_rbar);
    }

    if (ptid < 32) {
        mbar_wait_cluster(bar_r);
        float4 v[8];
        #pragma unroll
        for (int i = 0; i < 8; i++)
            asm volatile("ld.shared.v4.f32 {%0,%1,%2,%3}, [%4];" : "=f"(v[i].x), "=f"(v[i].y), "=f"(v[i].z), "=f"(v[i].w)
                         : "r"(s_rin + i * 512) : "memory");
        const float s0 = ((v[0].x + v[1].x) + (v[2].x + v[3].x)) + ((v[4].x + v[5].x) + (v[6].x + v[7].x));
        const float s1 = ((v[0].y + v[1].y) + (v[2].y + v[3].y)) + ((v[4].y + v[5].y) + (v[6].y + v[7].y));
        const float s2 = ((v[0].z + v[1].z) + (v[2].z + v[3].z)) + ((v[4].z + v[5].z) + (v[6].z + v[7].z));
        const float s3 = ((v[0].w + v[1].w) + (v[2].w + v[3].w)) + ((v[4].w + v[5].w) + (v[6].w + v[7].w));
        const bool p1 = ptid & 8, p2 = ptid & 16;
        float a = p1 ? s1 : s0, bq = p1 ? s3 : s2;
        a += __shfl_xor_sync(0xffffffffu, p1 ? s0 : s1, 8);
        bq += __shfl_xor_sync(0xffffffffu, p1 ? s2 : s3, 8);
        float r = p2 ? bq : a;
        r += __shfl_xor_sync(0xffffffffu, p2 ? a : bq, 16);
        *outp = __float2bfloat16_rn(r + resid);
        if (cta == 0 && lane == 0) st_rlx(&g_epoch, *epoch_s + 1u);
    }
}

typedef CUresult (*EncodeFn)(CUtensorMap*, CUtensorMapDataType, cuuint32_t, void*, const cuuint64_t*, const cuuint64_t*,
                             const cuuint32_t*, const cuuint32_t*, CUtensorMapInterleave, CUtensorMapSwizzle,
                             CUtensorMapL2promotion, CUtensorMapFloatOOBfill);

void encode(EncodeFn fn, CUtensorMap* m, const void* p, int rank, const cuuint64_t* dims, const cuuint64_t* strides,
            const cuuint32_t* box, CUtensorMapSwizzle sw,
            CUtensorMapL2promotion promo = CU_TENSOR_MAP_L2_PROMOTION_L2_256B) {
    const cuuint32_t es[3] = {1, 1, 1};
    fn(m, CU_TENSOR_MAP_DATA_TYPE_BFLOAT16, rank, const_cast<void*>(p), dims, strides, box, es,
       CU_TENSOR_MAP_INTERLEAVE_NONE, sw, promo, CU_TENSOR_MAP_FLOAT_OOB_FILL_NONE);
}

}

extern "C" void kernel_launch(void* const* d_in, const int* in_sizes, int n_in, void* d_out, int out_size) {
    (void)in_sizes; (void)n_in; (void)out_size;
    static EncodeFn fn = nullptr;
    if (!fn) {
        cudaDriverEntryPointQueryResult qr;
        cudaGetDriverEntryPoint("cuTensorMapEncodeTiled", (void**)&fn, cudaEnableDefault, &qr);
        cudaFuncSetAttribute(fused_decode_kernel, cudaFuncAttributeMaxDynamicSharedMemorySize, SMEM_BYTES);
        cudaFuncSetAttribute(fused_decode_kernel, cudaFuncAttributeNonPortableClusterSizeAllowed, 1);
    }
    Maps m;
    {
        const cuuint64_t d[3] = {64, 64ull * 4096, 2}, s[2] = {256, 128};
        const cuuint32_t bx[3] = {64, 64, 2};
        encode(fn, &m.k, d_in[1], 3, d, s, bx, CU_TENSOR_MAP_SWIZZLE_128B);
        encode(fn, &m.v, d_in[2], 3, d, s, bx, CU_TENSOR_MAP_SWIZZLE_128B);
    }
    { const cuuint64_t d[3] = {64, 8, 8}, s[2] = {1024, 128}; const cuuint32_t bx[3] = {64, 8, 8};
      encode(fn, &m.x, d_in[0], 3, d, s, bx, CU_TENSOR_MAP_SWIZZLE_128B); }
    { const cuuint64_t d[2] = {4096, 512}, s[1] = {8192}; const cuuint32_t bx[2] = {32, 256};
      encode(fn, &m.wq, d_in[3], 2, d, s, bx, CU_TENSOR_MAP_SWIZZLE_64B); }
    { const cuuint64_t d[2] = {512, 4096}, s[1] = {1024}; const cuuint32_t bx[2] = {64, 128};
      encode(fn, &m.wo, d_in[4], 2, d, s, bx, CU_TENSOR_MAP_SWIZZLE_128B, CU_TENSOR_MAP_L2_PROMOTION_L2_128B); }
    { const cuuint64_t d[2] = {1792, 512}, s[1] = {3584}; const cuuint32_t bx[2] = {16, 256};
      encode(fn, &m.w1, d_in[6], 2, d, s, bx, CU_TENSOR_MAP_SWIZZLE_32B); }
    { const cuuint64_t d[2] = {512, 1792}, s[1] = {1024}; const cuuint32_t bx[2] = {64, 112};
      encode(fn, &m.w2, d_in[7], 2, d, s, bx, CU_TENSOR_MAP_SWIZZLE_128B, CU_TENSOR_MAP_L2_PROMOTION_L2_128B); }

    cudaLaunchConfig_t cfg = {};
    cfg.gridDim = dim3(NCTA); cfg.blockDim = dim3(NTHREADS); cfg.dynamicSmemBytes = SMEM_BYTES;
    cfg.stream = cudaStreamPerThread;
    cudaLaunchAttribute at[2];
    at[0].id = cudaLaunchAttributeClusterDimension;
    at[0].val.clusterDim.x = CLUSTER; at[0].val.clusterDim.y = 1; at[0].val.clusterDim.z = 1;
    at[1].id = cudaLaunchAttributeClusterSchedulingPolicyPreference;
    at[1].val.clusterSchedulingPolicyPreference = cudaClusterSchedulingPolicyLoadBalancing;
    cfg.attrs = at; cfg.numAttrs = 2;
    cudaLaunchKernelEx(&cfg, fused_decode_kernel, m, (const char*)d_in[3], (__nv_bfloat16*)d_out);
}
```

```cpp
#include <cuda_runtime.h>
#include <cuda_bf16.h>
#include <cuda.h>
#include <stdint.h>

namespace {

constexpr int NCTA = 128;
constexpr int CLUSTER = 16;
constexpr int NTHREADS = 288;
constexpr int CHUNK = 16384;
constexpr int NSLOT = 6;
constexpr int NCHUNK = 22;
constexpr int C_K = 3, C_V = 11, C_W2 = 19, C_WO = 20;
constexpr int DEPTH = 4;
__host__ __device__ constexpr int clk_count(int j) { return j == 18 ? 14 : j == 15 ? 15 : 12; }
constexpr int PF_BYTES = 8192;

constexpr int RED_PITCH = 36;
constexpr int OFF_U = NSLOT * CHUNK;
constexpr int OFF_X = OFF_U;
constexpr int OFF_RED = OFF_U;
constexpr int OFF_P = OFF_U;
constexpr int OFF_OB = OFF_U + 4096;
constexpr int OFF_RIN = OFF_U + 9216;
constexpr int OFF_Q = OFF_RIN + 4096;
constexpr int OFF_OST = OFF_Q;
constexpr int OFF_H = OFF_Q + 1024;
constexpr int OFF_ML = OFF_H + 2176;
constexpr int OFF_STAT = OFF_ML + 32;
constexpr int OFF_BAR = OFF_STAT + 336;
constexpr int SMEM_BYTES = OFF_BAR + 49 * 8;
static_assert(2 * (SMEM_BYTES + 1024) <= 233472, "two CTAs per SM");

struct Maps { CUtensorMap x, wq, k, v, w1, wo, w2; };

__device__ unsigned int g_epoch;
__device__ __align__(128) uint32_t g_o[2 * 8 * 32 * 64];
__device__ __align__(128) uint32_t g_h[8 * 896];

constexpr uint32_t BAR_LIMIT = 1u << 20, POLL_LIMIT = 1u << 23;

__device__ __forceinline__ uint32_t smem_u32(const void* p) { return (uint32_t)__cvta_generic_to_shared(p); }
__device__ __forceinline__ void mbar_init(uint32_t bar, uint32_t cnt) {
    asm volatile("mbarrier.init.shared::cta.b64 [%0], %1;" :: "r"(bar), "r"(cnt) : "memory");
}
__device__ __forceinline__ void mbar_expect(uint32_t bar, uint32_t bytes) {
    asm volatile("mbarrier.arrive.expect_tx.shared::cta.b64 _, [%0], %1;" :: "r"(bar), "r"(bytes) : "memory");
}
__device__ __forceinline__ void mbar_arrive(uint32_t bar) {
    asm volatile("mbarrier.arrive.shared::cta.b64 _, [%0];" :: "r"(bar) : "memory");
}
template <int PHASE = 0>
__device__ __forceinline__ bool mbar_try(uint32_t bar) {
    uint32_t done;
    asm volatile("{\n.reg .pred p;\nmbarrier.try_wait.parity.shared::cta.b64 p, [%1], %2;\nselp.u32 %0, 1, 0, p;\n}"
                 : "=r"(done) : "r"(bar), "n"(PHASE) : "memory");
    return done;
}
__device__ __forceinline__ bool mbar_test(uint32_t bar) {
    uint32_t done;
    asm volatile("{\n.reg .pred p;\nmbarrier.test_wait.parity.shared::cta.b64 p, [%1], 0;\nselp.u32 %0, 1, 0, p;\n}"
                 : "=r"(done) : "r"(bar) : "memory");
    return done;
}
__device__ __forceinline__ void mbar_wait(uint32_t bar) {
    for (uint32_t n = 0; !mbar_try(bar); ) if (++n > BAR_LIMIT) __trap();
}
__device__ __forceinline__ bool mbar_try_cluster(uint32_t bar) {
    uint32_t done;
    asm volatile("{\n.reg .pred p;\nmbarrier.try_wait.parity.acquire.cluster.shared::cta.b64 p, [%1], 0;\nselp.u32 %0, 1, 0, p;\n}"
                 : "=r"(done) : "r"(bar) : "memory");
    return done;
}
__device__ __forceinline__ void mbar_wait_cluster(uint32_t bar) {
    for (uint32_t n = 0; !mbar_try_cluster(bar); ) if (++n > BAR_LIMIT) __trap();
}
__device__ __forceinline__ uint32_t mapa(uint32_t addr, uint32_t rank) {
    uint32_t r; asm("mapa.shared::cluster.u32 %0, %1, %2;" : "=r"(r) : "r"(addr), "r"(rank)); return r;
}
__device__ __forceinline__ void tick_remote(uint32_t bar) {
    asm volatile("mbarrier.arrive.relaxed.cluster.shared::cluster.b64 _, [%0];" :: "r"(bar) : "memory");
}
__device__ __forceinline__ void st_async2(uint32_t dst, uint32_t a, uint32_t b, uint32_t bar) {
    asm volatile("st.async.weak.shared::cluster.mbarrier::complete_tx::bytes.v2.b32 [%0], {%1,%2}, [%3];"
                 :: "r"(dst), "r"(a), "r"(b), "r"(bar) : "memory");
}
__device__ __forceinline__ void st_async4(uint32_t dst, uint32_t a, uint32_t b, uint32_t c, uint32_t d, uint32_t bar) {
    asm volatile("st.async.weak.shared::cluster.mbarrier::complete_tx::bytes.v4.b32 [%0], {%1,%2,%3,%4}, [%5];"
                 :: "r"(dst), "r"(a), "r"(b), "r"(c), "r"(d), "r"(bar) : "memory");
}
__device__ __forceinline__ void tma2d(uint32_t dst, const CUtensorMap* m, int c0, int c1, uint32_t bar) {
    asm volatile("cp.async.bulk.tensor.2d.shared::cluster.global.mbarrier::complete_tx::bytes [%0], [%1, {%3, %4}], [%2];"
                 :: "r"(dst), "l"(m), "r"(bar), "r"(c0), "r"(c1) : "memory");
}
__device__ __forceinline__ void tma3d(uint32_t dst, const CUtensorMap* m, int c0, int c1, int c2, uint32_t bar) {
    asm volatile("cp.async.bulk.tensor.3d.shared::cluster.global.mbarrier::complete_tx::bytes [%0], [%1, {%3, %4, %5}], [%2];"
                 :: "r"(dst), "l"(m), "r"(bar), "r"(c0), "r"(c1), "r"(c2) : "memory");
}
__device__ __forceinline__ void l2_prefetch(const void* src, uint32_t bytes) {
    asm volatile("cp.async.bulk.prefetch.L2.global [%0], %1;" :: "l"(src), "r"(bytes) : "memory");
}
__device__ __forceinline__ void ldsm4(uint32_t (&r)[4], uint32_t addr) {
    asm volatile("ldmatrix.sync.aligned.m8n8.x4.shared.b16 {%0,%1,%2,%3}, [%4];"
                 : "=r"(r[0]), "=r"(r[1]), "=r"(r[2]), "=r"(r[3]) : "r"(addr) : "memory");
}
__device__ __forceinline__ void ldsm4t(uint32_t (&r)[4], uint32_t addr) {
    asm volatile("ldmatrix.sync.aligned.m8n8.x4.trans.shared.b16 {%0,%1,%2,%3}, [%4];"
                 : "=r"(r[0]), "=r"(r[1]), "=r"(r[2]), "=r"(r[3]) : "r"(addr) : "memory");
}
__device__ __forceinline__ void mma16816(float (&d)[4], const uint32_t (&a)[4], uint32_t b0, uint32_t b1) {
    asm volatile("mma.sync.aligned.m16n8k16.row.col.f32.bf16.bf16.f32 {%0,%1,%2,%3}, {%4,%5,%6,%7}, {%8,%9}, {%0,%1,%2,%3};"
                 : "+f"(d[0]), "+f"(d[1]), "+f"(d[2]), "+f"(d[3])
                 : "r"(a[0]), "r"(a[1]), "r"(a[2]), "r"(a[3]), "r"(b0), "r"(b1));
}
__device__ __forceinline__ uint32_t movtrans(uint32_t a) {
    uint32_t d;
    asm volatile("movmatrix.sync.aligned.m8n8.trans.b16 %0, %1;" : "=r"(d) : "r"(a));
    return d;
}
__device__ __forceinline__ uint32_t pack_bf16(float lo, float hi) {
    uint32_t d;
    asm("cvt.rn.bf16x2.f32 %0, %1, %2;" : "=r"(d) : "f"(hi), "f"(lo));
    return d;
}
__device__ __forceinline__ float bf16r(float x) { return __bfloat162float(__float2bfloat16_rn(x)); }
__device__ __forceinline__ float bf_lo(uint32_t u) { return __uint_as_float(u << 16); }
__device__ __forceinline__ float bf_hi(uint32_t u) { return __uint_as_float(u & 0xffff0000u); }
__device__ __forceinline__ uint32_t hadd2_bf16(uint32_t a, uint32_t b) {
    uint32_t d;
    asm("add.rn.bf16x2 %0, %1, %2;" : "=r"(d) : "r"(a), "r"(b));
    return d;
}
__device__ __forceinline__ uint32_t ld_rlx(const uint32_t* p) {
    uint32_t v; asm volatile("ld.relaxed.gpu.global.u32 %0, [%1];" : "=r"(v) : "l"(p) : "memory"); return v;
}
__device__ __forceinline__ void st_rlx(uint32_t* p, uint32_t v) {
    asm volatile("st.relaxed.gpu.global.u32 [%0], %1;" :: "l"(p), "r"(v) : "memory");
}
__device__ __forceinline__ uint4 ld_rlx_2x64(const void* p) {
    unsigned long long a, b;
    asm volatile("ld.relaxed.gpu.global.v2.b64 {%0,%1}, [%2];" : "=l"(a), "=l"(b) : "l"(p) : "memory");
    return make_uint4((uint32_t)a, (uint32_t)(a >> 32), (uint32_t)b, (uint32_t)(b >> 32));
}
__device__ __forceinline__ void st_rlx_2x64(void* p, const uint4& v) {
    asm volatile("st.relaxed.gpu.global.v2.b64 [%0], {%1,%2};" :: "l"(p),
                 "l"(((unsigned long long)v.y << 32) | v.x), "l"(((unsigned long long)v.w << 32) | v.z) : "memory");
}
__device__ __forceinline__ void st_rlx_64(void* p, uint32_t lo, uint32_t hi) {
    asm volatile("st.relaxed.gpu.global.b64 [%0], %1;" :: "l"(p), "l"(((unsigned long long)hi << 32) | lo) : "memory");
}
__device__ __forceinline__ bool tagged(const uint4& v, uint32_t tag) { return (((v.x ^ tag) | (v.z ^ tag)) & 1u) == 0u; }
__device__ __forceinline__ void sts128(uint32_t a, uint32_t x, uint32_t y, uint32_t z, uint32_t w) {
    asm volatile("st.shared.v4.b32 [%0], {%1,%2,%3,%4};" :: "r"(a), "r"(x), "r"(y), "r"(z), "r"(w) : "memory");
}
template <typename T> __device__ __forceinline__ void pin64(T*& p) { asm volatile("" : "+l"(p)); }
__device__ __forceinline__ void pin32(uint32_t& v) { asm volatile("" : "+r"(v)); }
__device__ __forceinline__ void cbar() { asm volatile("bar.sync 1, 256;" ::: "memory"); }
__device__ __forceinline__ float ex2(float x) { float y; asm("ex2.approx.ftz.f32 %0, %1;" : "=f"(y) : "f"(x)); return y; }

__global__ void __launch_bounds__(NTHREADS, 2)
fused_decode_kernel(const __grid_constant__ Maps maps, const char* __restrict__ wq_raw, __nv_bfloat16* __restrict__ out)
{
    extern __shared__ __align__(1024) char smp[];
    const uint32_t sm = smem_u32(smp);
    const int tid = threadIdx.x, warp = tid >> 5, lane = tid & 31;
    const int cta = blockIdx.x, g = cta >> 4, c = cta & 15, b = c >> 1, half = c & 1;
    const bool ffn = g < 7;
    const uint32_t bar_full = sm + OFF_BAR, bar_empty = bar_full + NCHUNK * 8;
    const uint32_t bar_q = bar_empty + 16 * 8, bar_ml = bar_q + 8, bar_r = bar_q + 16, bar_x = bar_q + 24, bar_go = bar_q + 32;
    const uint32_t bar_clk = bar_q + 40 - 13 * 8;

    if (warp == 8) {
        if (lane == 0) {
            mbar_init(bar_x, 1); mbar_init(bar_full, 1); mbar_init(bar_full + 8, 1);
            asm volatile("fence.proxy.async.shared::cta;" ::: "memory");
            mbar_expect(bar_full, CHUNK); tma2d(sm, &maps.wq, cta * 32, 0, bar_full);
            mbar_expect(bar_x, 8192); tma3d(sm + OFF_X, &maps.x, 0, 0, 0, bar_x);
            mbar_expect(bar_full + 8, CHUNK); tma2d(sm + CHUNK, &maps.wq, cta * 32, 256, bar_full + 8);
            if (sm & 1023u) __trap();
            #pragma unroll
            for (int s = 2; s < NCHUNK; s++) mbar_init(bar_full + s * 8, 1);
            #pragma unroll
            for (int s = 0; s < 16; s++) mbar_init(bar_empty + s * 8, (s < 2 || (s >= C_K && s < C_V)) ? 4 : 8);
            mbar_init(bar_q, 1); mbar_init(bar_ml, 1); mbar_init(bar_r, 1); mbar_init(bar_go, 1);
            #pragma unroll
            for (int s = 13; s < C_W2; s++) mbar_init(bar_clk + s * 8, clk_count(s));
            mbar_expect(bar_q, 1024); mbar_expect(bar_ml, 32); mbar_expect(bar_r, 4096);
            asm volatile("fence.mbarrier_init.release.cluster;" ::: "memory");
            asm volatile("fence.proxy.async.shared::cta;" ::: "memory");
        }
        __syncwarp();
        asm volatile("barrier.cluster.arrive.relaxed.aligned;" ::: "memory");
        asm volatile("bar.arrive 2, %0;" :: "n"(NTHREADS) : "memory");
        if (lane == 0) {
            if (ffn) {
                mbar_expect(bar_full + 16, CHUNK);
                tma2d(sm + 2 * CHUNK, &maps.w1, cta * 16, 0, bar_full + 16);
                tma2d(sm + 2 * CHUNK + 8192, &maps.w1, cta * 16, 256, bar_full + 16);
            } else mbar_arrive(bar_full + 16);
            const int row0 = (b * 8 + g) * 4096 + 3072 + half * 512;
            uint32_t dst = sm + C_K * CHUNK;
            #pragma unroll 1
            for (int ch = C_K; ch < NCHUNK; ch++) {
                if (ch >= 17) mbar_wait(bar_clk + (ch < C_W2 ? ch - 4 : ch - 3) * 8);
                else if (ch >= DEPTH) mbar_wait(bar_full + (ch - DEPTH) * 8);
                if (ch >= NSLOT) mbar_wait(bar_empty + (ch - NSLOT) * 8);
                const uint32_t bar = bar_full + ch * 8;
                if (ch < C_W2) {
                    mbar_expect(bar, CHUNK);
                    tma3d(dst, ch < C_V ? &maps.k : &maps.v, 0, row0 + ((ch - C_K) & 7) * 64, 0, bar);
                } else {
                    mbar_expect(bar, ch == C_W2 ? 14336 : CHUNK);
                    tma2d(dst, ch == C_W2 ? &maps.w2 : &maps.wo, g * 64,
                          ch == C_W2 ? c * 112 : c * 256 + (ch - C_WO) * 128, bar);
                }
                dst = (dst == sm + (NSLOT - 1) * CHUNK) ? sm : dst + CHUNK;
            }
            mbar_wait(bar_clk + 15 * 8);
            mbar_arrive(bar_go);
            #pragma unroll
            for (int s = 13; s < C_W2; s++)
                asm volatile("mbarrier.arrive.shared::cta.b64 _, [%0], %1;" :: "r"(bar_clk + s * 8), "r"(2 * clk_count(s) - 16) : "memory");
            #pragma unroll
            for (int s = 13; s < C_W2; s++)
                for (uint32_t n = 0; !mbar_try<1>(bar_clk + s * 8); ) if (++n > BAR_LIMIT) __trap();
        }
        __syncwarp();
        asm volatile("barrier.cluster.wait.aligned;" ::: "memory");
        return;
    }

    if (tid == 0) l2_prefetch(wq_raw + (size_t)cta * 32768, PF_BYTES);
    asm volatile("barrier.cluster.arrive.relaxed.aligned;" ::: "memory");
    const int gl = lane >> 2, t = lane & 3;
    float* lnst = reinterpret_cast<float*>(smp + OFF_STAT + 256);
    volatile uint32_t* epoch_s = reinterpret_cast<volatile uint32_t*>(smp + OFF_STAT + 320);
    const int ru = lane & 7, rp = lane >> 3;
    const int ob = 2 * (ru & 3) + (rp & 1);
    const int ocol = g * 64 + (c >> 2) * 16 + 2 * (c & 3) + (ru >> 2) + 8 * (rp >> 1);
    uint32_t epoch_r = 0;
    if (tid == 64) epoch_r = ld_rlx(&g_epoch);
    asm volatile("bar.sync 2, %0;" :: "n"(NTHREADS) : "memory");
    if (tid == 64) *epoch_s = epoch_r;
    mbar_wait(bar_x);
    uint32_t xf[8];
    #pragma unroll
    for (int j = 0; j < 8; j++)
        xf[j] = *reinterpret_cast<const uint32_t*>(smp + OFF_X + warp * 1024 + gl * 128 + ((j ^ gl) << 4) + t * 4);
    const float resid = __bfloat162float(*reinterpret_cast<const __nv_bfloat16*>(
        smp + OFF_X + g * 1024 + ob * 128 + ((((ocol >> 3) & 7) ^ ob) << 4) + (ocol & 7) * 2));
    {
        const char* xr = smp + OFF_X + (lane >> 3) * 1024 + warp * 128 + (lane & 7) * 16;
        const uint4 xa = *reinterpret_cast<const uint4*>(xr), xb = *reinterpret_cast<const uint4*>(xr + 4096);
        const float sh = bf_lo(*reinterpret_cast<const uint32_t*>(smp + OFF_X + warp * 128));
        const uint32_t w[8] = {xa.x, xa.y, xa.z, xa.w, xb.x, xb.y, xb.z, xb.w};
        float s4[4] = {}, q4[4] = {};
        #pragma unroll
        for (int j = 0; j < 8; j++) {
            const float lo = bf_lo(w[j]) - sh, hi = bf_hi(w[j]) - sh;
            s4[j & 3] += lo + hi;
            q4[j & 3] = fmaf(lo, lo, fmaf(hi, hi, q4[j & 3]));
        }
        float s = (s4[0] + s4[1]) + (s4[2] + s4[3]), q2 = (q4[0] + q4[1]) + (q4[2] + q4[3]);
        #pragma unroll
        for (int o = 16; o > 0; o >>= 1) {
            s += __shfl_xor_sync(0xffffffffu, s, o);
            q2 += __shfl_xor_sync(0xffffffffu, q2, o);
        }
        const float ms = s * (1.f / 512.f), mean = sh + ms;
        q2 = fmaxf(fmaf(-ms, s, q2), 0.f);
        const float den = bf16r(__fsqrt_rn(bf16r(bf16r(q2 * (1.f / 512.f)) + 1e-5f)));
        if (lane == 0) *reinterpret_cast<float2*>(lnst + warp * 2) = make_float2(bf16r(mean), __frcp_rn(den));
    }
    cbar();
    {
        const float2 st = *reinterpret_cast<const float2*>(lnst + gl * 2);
        #pragma unroll
        for (int j = 0; j < 8; j++)
            xf[j] = pack_bf16(bf16r(bf_lo(xf[j]) - st.x) * st.y, bf16r(bf_hi(xf[j]) - st.x) * st.y);
    }
    const uint32_t tag = (*epoch_s + 1u) & 1u;

    float* red = reinterpret_cast<float*>(smp + OFF_RED);
    const int mj = lane >> 3, mr = lane & 7;
    float* r0 = red + (warp * 8 + 2 * t) * RED_PITCH + gl;
    {
        float aq[2][4] = {};
        mbar_wait(bar_full + (warp >> 2) * 8);
        const uint32_t wqs = sm + (warp >> 2) * CHUNK;
        #pragma unroll
        for (int s = 0; s < 4; s++) {
            const int row = (warp & 3) * 64 + s * 16 + (mj >> 1) * 8 + mr;
            #pragma unroll
            for (int j = 0; j < 2; j++) {
                uint32_t a[4];
                ldsm4t(a, wqs + row * 64 + (((2 * j + (mj & 1)) ^ ((row >> 1) & 3)) << 4));
                mma16816(aq[j], a, xf[2 * s], xf[2 * s + 1]);
            }
        }
        __syncwarp();
        if (lane == 0) mbar_arrive(bar_empty + (warp >> 2) * 8);
        #pragma unroll
        for (int j = 0; j < 2; j++) {
            r0[j * 16] = aq[j][0]; r0[RED_PITCH + j * 16] = aq[j][1];
            r0[j * 16 + 8] = aq[j][2]; r0[RED_PITCH + j * 16 + 8] = aq[j][3];
        }
    }
    cbar();
    asm volatile("barrier.cluster.wait.aligned;" ::: "memory");
    if (warp < 4) {
        const int bb = tid >> 4, wd = tid & 15;
        const int col = (wd >> 3) * 16 + ((wd >> 1) & 3) * 2 + (wd & 1) * 8;
        float s0 = 0.f, s1 = 0.f;
        #pragma unroll
        for (int w = 0; w < 8; w++) {
            const float2 f = *reinterpret_cast<const float2*>(red + (w * 8 + bb) * RED_PITCH + col);
            s0 += f.x; s1 += f.y;
        }
        const uint32_t u = pack_bf16(s0, s1);
        const int q0 = (lane & 16) + (lane & 3) * 4;
        const uint32_t u0 = __shfl_sync(0xffffffffu, u, q0), u1 = __shfl_sync(0xffffffffu, u, q0 + 1);
        const uint32_t u2 = __shfl_sync(0xffffffffu, u, q0 + 2), u3 = __shfl_sync(0xffffffffu, u, q0 + 3);
        if (wd < 8) {
            const uint32_t rank = 2 * bb + (wd >> 2);
            st_async4(mapa(sm + OFF_Q + c * 64 + (wd & 3) * 16, rank), u0, u1, u2, u3, mapa(bar_q, rank));
        }
    }
    if (ffn) {
        float ah[4] = {};
        mbar_wait(bar_full + 2 * 8);
        const uint32_t w1s = sm + 2 * CHUNK;
        #pragma unroll
        for (int s = 0; s < 4; s++) {
            const int row = warp * 64 + s * 16 + (mj >> 1) * 8 + mr;
            uint32_t a[4];
            ldsm4t(a, w1s + row * 32 + (((mj & 1) ^ ((row >> 2) & 1)) << 4));
            mma16816(ah, a, xf[2 * s], xf[2 * s + 1]);
        }
        __syncwarp();
        if (lane == 0) mbar_arrive(bar_empty + 2 * 8);
        cbar();
        r0[0] = ah[0]; r0[RED_PITCH] = ah[1]; r0[8] = ah[2]; r0[RED_PITCH + 8] = ah[3];
        cbar();
        if (warp >= 6) {
            const int bb = (tid & 63) >> 3, wd = tid & 7;
            float s0 = 0.f, s1 = 0.f;
            #pragma unroll
            for (int w = 0; w < 8; w++) {
                const float2 f = *reinterpret_cast<const float2*>(red + (w * 8 + bb) * RED_PITCH + 2 * wd);
                s0 += f.x; s1 += f.y;
            }
            s0 = bf16r(s0); s1 = bf16r(s1);
            s0 = __fdividef(s0, 1.f + __expf(-s0)); s1 = __fdividef(s1, 1.f + __expf(-s1));
            const uint32_t u = pack_bf16(s0, s1);
            const uint32_t un = __shfl_down_sync(0xffffffffu, u, 1);
            if (!(wd & 1)) st_rlx_64(g_h + bb * 896 + cta * 8 + wd, (u & ~1u) | tag, un);
        }
    } else {
        __syncwarp();
        if (lane == 0) mbar_arrive(bar_empty + 2 * 8);
    }

    float sc[4][4];
    float m0 = -INFINITY, m1 = -INFINITY;
    {
        mbar_wait_cluster(bar_q);
        uint32_t qb[8][2];
        #pragma unroll
        for (int s = 0; s < 8; s++) {
            const uint2 v = *reinterpret_cast<const uint2*>(smp + OFF_Q + (((gl & 3) * 8 + s) * 4 + t) * 8);
            qb[s][0] = v.x; qb[s][1] = v.y;
        }
        const uint32_t koff = ((warp & 3) * 16 + (mj & 1) * 8 + mr) * 128;
        #pragma unroll
        for (int i = 0; i < 4; i++) {
            const int ck = C_K + 2 * i + (warp >> 2);
            mbar_wait(bar_full + ck * 8);
            const uint32_t ks = sm + (ck % NSLOT) * CHUNK + koff;
            float s0[4] = {}, s1[4] = {};
            #pragma unroll
            for (int s = 0; s < 4; s++) {
                const uint32_t sw = ((2 * s + (mj >> 1)) ^ mr) << 4;
                uint32_t a[4], a2[4];
                ldsm4(a, ks + sw);
                ldsm4(a2, ks + 8192 + sw);
                mma16816(s0, a, qb[s][0], qb[s][1]);
                mma16816(s1, a2, qb[4 + s][0], qb[4 + s][1]);
            }
            __syncwarp();
            if (lane == 0) mbar_arrive(bar_empty + ck * 8);
            #pragma unroll
            for (int k = 0; k < 4; k++) sc[i][k] = bf16r(bf16r(s0[k] + s1[k]) * 0.08838834764831845f);
            m0 = fmaxf(m0, fmaxf(sc[i][0], sc[i][2]));
            m1 = fmaxf(m1, fmaxf(sc[i][1], sc[i][3]));
        }
    }
    float* wmax = reinterpret_cast<float*>(smp + OFF_STAT);
    float* wsum = wmax + 32;
    constexpr float L2E = 1.4426950408889634f;
    {
        #pragma unroll
        for (int o = 4; o < 32; o <<= 1) {
            m0 = fmaxf(m0, __shfl_xor_sync(0xffffffffu, m0, o));
            m1 = fmaxf(m1, __shfl_xor_sync(0xffffffffu, m1, o));
        }
        if (lane < 2) *reinterpret_cast<float2*>(wmax + warp * 4 + 2 * lane) = make_float2(m0, m1);
        cbar();
        #pragma unroll
        for (int w = 0; w < 8; w++) {
            const float2 f = *reinterpret_cast<const float2*>(wmax + w * 4 + 2 * (t & 1));
            m0 = fmaxf(m0, f.x); m1 = fmaxf(m1, f.y);
        }
        float l0 = 0.f, l1 = 0.f;
        uint32_t pw[4][2];
        #pragma unroll
        for (int i = 0; i < 4; i++) {
            const float p0 = ex2((sc[i][0] - m0) * L2E), p1 = ex2((sc[i][1] - m1) * L2E);
            const float p2 = ex2((sc[i][2] - m0) * L2E), p3 = ex2((sc[i][3] - m1) * L2E);
            l0 += p0 + p2; l1 += p1 + p3;
            pw[i][0] = movtrans(pack_bf16(p0, p1));
            pw[i][1] = movtrans(pack_bf16(p2, p3));
        }
        if (lane < 16) {
            char* pd = smp + OFF_P + ((warp >> 2) * 2 + ((warp >> 1) & 1)) * 256 + lane * 16 + (warp & 1) * 8;
            #pragma unroll
            for (int i = 0; i < 4; i++) *reinterpret_cast<uint2*>(pd + i * 1024) = make_uint2(pw[i][0], pw[i][1]);
        }
        #pragma unroll
        for (int o = 4; o < 32; o <<= 1) {
            l0 += __shfl_xor_sync(0xffffffffu, l0, o);
            l1 += __shfl_xor_sync(0xffffffffu, l1, o);
        }
        if (lane < 2) *reinterpret_cast<float2*>(wsum + warp * 4 + 2 * lane) = make_float2(l0, l1);
    }
    cbar();
    float l0 = 0.f, l1 = 0.f;
    #pragma unroll
    for (int w = 0; w < 8; w++) {
        const float2 f = *reinterpret_cast<const float2*>(wsum + w * 4 + 2 * (t & 1));
        l0 += f.x; l1 += f.y;
    }
    if (tid < 2) {
        const uint32_t dst = mapa(sm + OFF_ML + tid * 8, c ^ 1), bar = mapa(bar_ml, c ^ 1);
        st_async2(dst, __float_as_uint(m0), __float_as_uint(m1), bar);
        st_async2(dst + 16, __float_as_uint(l0), __float_as_uint(l1), bar);
    }

    const uint32_t* op = g_o + (((tid >> 4) & 7) * 32 + 2 * c + (tid >> 7)) * 64 + (tid & 15) * 4;
    uint32_t* opub = g_o + ((half * 8 + b) * 32 + g * 4) * 64 + (tid & 63) * 4;
    __nv_bfloat16* outp = out + ob * 512 + ocol;
    uint32_t s_ost = sm + OFF_OST + gl * 256 + (t * 4 + ((warp >> 1) ^ (t & 2))) * 16 + (warp & 1) * 8;
    uint32_t s_rdst = mapa(sm + OFF_RIN + (c * 2 + (warp >> 2)) * 128 + ru * 16, (warp & 3) * 4 + rp);
    uint32_t s_rbar = mapa(bar_r, (warp & 3) * 4 + rp);
    uint32_t s_obw = sm + OFF_OB + (tid >> 4) * 320 + (((tid & 15) ^ ((tid >> 4) & 1)) << 4);
    uint32_t s_obr = sm + OFF_OB + gl * 320 + t * 64 + ((((warp >> 2) * 2) ^ (t & 2) ^ (gl & 1)) << 4);
    const int hb = min(tid / 14, 7), hpc = tid - (tid / 14) * 14;
    const uint32_t* hp = g_h + hb * 896 + c * 56 + hpc * 4;
    uint32_t s_h = sm + OFF_H + hb * 272 + hpc * 16;
    pin64(op); pin64(opub); pin64(outp); pin64(hp);
    uint32_t aoff = sm + (warp >> 2) * 8192 + ((mj >> 1) * 8 + mr) * 128 + (((2 * (warp & 3) + (mj & 1)) ^ mr) << 4);
    uint32_t s_hs = sm + OFF_H + (gl * 68 + (warp >> 2) * 32 + t) * 4;
    uint32_t s_rin = sm + OFF_RIN + lane * 16;
    uint32_t ptid = tid;
    uint32_t s_clk = mapa(bar_clk + C_V * 8, tid & 15);
    pin32(s_ost); pin32(s_rdst); pin32(s_rbar); pin32(s_obw); pin32(s_obr); pin32(s_h);
    pin32(aoff); pin32(s_hs); pin32(s_rin); pin32(ptid); pin32(s_clk);
    uint4 hv = make_uint4(tag, 0u, tag, 0u);
    if (tid < 112) hv = ld_rlx_2x64(hp);
    if (tid < 64) st_rlx_2x64(opub, make_uint4(tag ^ 1u, 0u, tag ^ 1u, 0u));

    float f0 = 0.f, f1 = 0.f;
    float oc[4][4] = {};
    {
        const int ach = 2 * warp + (mj & 1);
        uint32_t voff = (ach >> 3) * 8192 + ((mj >> 1) * 8 + mr) * 128 + (((ach & 7) ^ mr) << 4);
        pin32(voff);
        const uint4* pfp = reinterpret_cast<const uint4*>(smp + OFF_P) + (lane & 15);
        uint32_t vs = sm + (C_V % NSLOT) * CHUNK;
        #pragma unroll 1
        for (int j = 0; j < 8; j++) {
            const uint4 pa = pfp[j * 32], pb = pfp[j * 32 + 16];
            if (j == 6) {
                for (uint32_t n = 0; !tagged(hv, tag); ) {
                    hv = ld_rlx_2x64(hp);
                    if (++n > POLL_LIMIT) __trap();
                }
                if (tid < 112) sts128(s_h, hv.x, hv.y, hv.z, hv.w);
                __syncwarp();
                mbar_wait_cluster(bar_ml);
                const float* pm = reinterpret_cast<const float*>(smp + OFF_ML) + (t & 1) * 2;
                const float mo0 = pm[0], mo1 = pm[1];
                const float mt0 = fmaxf(m0, mo0), mt1 = fmaxf(m1, mo1);
                const float e0 = ex2((m0 - mt0) * L2E), e1 = ex2((m1 - mt1) * L2E);
                f0 = __fdividef(e0, l0 * e0 + pm[4] * ex2((mo0 - mt0) * L2E));
                f1 = __fdividef(e1, l1 * e1 + pm[5] * ex2((mo1 - mt1) * L2E));
            }
            mbar_wait(bar_full + (C_V + j) * 8);
            if (j >= 2 && j != 4 && ptid >= 240) tick_remote(s_clk + j * 8);
            uint32_t a[4][4];
            #pragma unroll
            for (int s = 0; s < 4; s++) ldsm4t(a[s], vs + voff + s * 2048);
            mma16816(oc[0], a[0], pa.x, pa.y);
            mma16816(oc[1], a[1], pa.z, pa.w);
            mma16816(oc[2], a[2], pb.x, pb.y);
            mma16816(oc[3], a[3], pb.z, pb.w);
            __syncwarp();
            if (j < 5 && lane == 0) mbar_arrive(bar_empty + (C_V + j) * 8);
            vs = (vs == sm + (NSLOT - 1) * CHUNK) ? sm : vs + CHUNK;
        }
    }
    {
        const float o0 = (oc[0][0] + oc[1][0]) + (oc[2][0] + oc[3][0]);
        const float o1 = (oc[0][1] + oc[1][1]) + (oc[2][1] + oc[3][1]);
        const float o2 = (oc[0][2] + oc[1][2]) + (oc[2][2] + oc[3][2]);
        const float o3 = (oc[0][3] + oc[1][3]) + (oc[2][3] + oc[3][3]);
        const uint32_t u0 = movtrans(pack_bf16(o0 * f0, o1 * f1));
        const uint32_t u1 = movtrans(pack_bf16(o2 * f0, o3 * f1));
        if (!(ptid & 16))
            asm volatile("st.shared.v2.b32 [%0], {%1,%2};" :: "r"(s_ost), "r"((u0 & ~1u) | tag), "r"(u1) : "memory");
        cbar();
        if (ptid < 64) st_rlx_2x64(opub, *reinterpret_cast<const uint4*>(smp + OFF_OST + ptid * 16));
        if (ptid >= 240) tick_remote(s_clk + 4 * 8);
    }

    {
        float ac[4][4] = {};
        mbar_wait(bar_full + C_W2 * 8);
        #pragma unroll
        for (int s = 0; s < 4; s++) {
            if (s < 3 || ptid < 128) {
                uint32_t a[4], h0, h1;
                ldsm4t(a, aoff + (C_W2 % NSLOT) * CHUNK + s * 2048);
                asm volatile("ld.shared.b32 %0, [%1];" : "=r"(h0) : "r"(s_hs + s * 32) : "memory");
                asm volatile("ld.shared.b32 %0, [%1];" : "=r"(h1) : "r"(s_hs + s * 32 + 16) : "memory");
                mma16816(ac[s], a, h0, h1);
            }
        }
        mbar_wait(bar_go);
        uint4 oa = ld_rlx_2x64(op), obv = ld_rlx_2x64(op + 16384);
        uint32_t wa[8][4];
        bool have0 = false, have1 = false;
        auto wo_part = [&](int i) {
            #pragma unroll
            for (int s = 0; s < 4; s++) ldsm4t(wa[i * 4 + s], aoff + (C_WO % NSLOT + i) * CHUNK + s * 2048);
        };
        for (uint32_t n = 0; ; ) {
            if (!have0 && __all_sync(0xffffffffu, mbar_test(bar_full + C_WO * 8))) { have0 = true; wo_part(0); }
            if (!have1 && __all_sync(0xffffffffu, mbar_test(bar_full + (C_WO + 1) * 8))) { have1 = true; wo_part(1); }
            if (++n > POLL_LIMIT) __trap();
            const bool na = !tagged(oa, tag), nb = !tagged(obv, tag);
            if (!__any_sync(0xffffffffu, na || nb)) break;
            if (na) oa = ld_rlx_2x64(op);
            if (nb) obv = ld_rlx_2x64(op + 16384);
        }
        sts128(s_obw, hadd2_bf16(oa.x, obv.x), hadd2_bf16(oa.y, obv.y), hadd2_bf16(oa.z, obv.z), hadd2_bf16(oa.w, obv.w));
        cbar();
        uint4 of[4];
        #pragma unroll
        for (int i = 0; i < 4; i++)
            asm volatile("ld.shared.v4.b32 {%0,%1,%2,%3}, [%4];" : "=r"(of[i].x), "=r"(of[i].y), "=r"(of[i].z), "=r"(of[i].w)
                         : "r"((s_obr ^ ((i & 1) << 4)) + (i >> 1) * 2560) : "memory");
        if (!have0) { mbar_wait(bar_full + C_WO * 8); wo_part(0); }
        mma16816(ac[0], wa[0], of[0].x, of[0].y);
        mma16816(ac[1], wa[1], of[0].z, of[0].w);
        mma16816(ac[2], wa[2], of[1].x, of[1].y);
        mma16816(ac[3], wa[3], of[1].z, of[1].w);
        if (!have1) { mbar_wait(bar_full + (C_WO + 1) * 8); wo_part(1); }
        mma16816(ac[0], wa[4], of[2].x, of[2].y);
        mma16816(ac[1], wa[5], of[2].z, of[2].w);
        mma16816(ac[2], wa[6], of[3].x, of[3].y);
        mma16816(ac[3], wa[7], of[3].z, of[3].w);
        st_async4(s_rdst,
                  __float_as_uint((ac[0][0] + ac[1][0]) + (ac[2][0] + ac[3][0])),
                  __float_as_uint((ac[0][1] + ac[1][1]) + (ac[2][1] + ac[3][1])),
                  __float_as_uint((ac[0][2] + ac[1][2]) + (ac[2][2] + ac[3][2])),
                  __float_as_uint((ac[0][3] + ac[1][3]) + (ac[2][3] + ac[3][3])), s_rbar);
    }

    if (ptid < 32) {
        mbar_wait_cluster(bar_r);
        float4 v[8];
        #pragma unroll
        for (int i = 0; i < 8; i++)
            asm volatile("ld.shared.v4.f32 {%0,%1,%2,%3}, [%4];" : "=f"(v[i].x), "=f"(v[i].y), "=f"(v[i].z), "=f"(v[i].w)
                         : "r"(s_rin + i * 512) : "memory");
        const float s0 = ((v[0].x + v[1].x) + (v[2].x + v[3].x)) + ((v[4].x + v[5].x) + (v[6].x + v[7].x));
        const float s1 = ((v[0].y + v[1].y) + (v[2].y + v[3].y)) + ((v[4].y + v[5].y) + (v[6].y + v[7].y));
        const float s2 = ((v[0].z + v[1].z) + (v[2].z + v[3].z)) + ((v[4].z + v[5].z) + (v[6].z + v[7].z));
        const float s3 = ((v[0].w + v[1].w) + (v[2].w + v[3].w)) + ((v[4].w + v[5].w) + (v[6].w + v[7].w));
        const bool p1 = ptid & 8, p2 = ptid & 16;
        float a = p1 ? s1 : s0, bq = p1 ? s3 : s2;
        a += __shfl_xor_sync(0xffffffffu, p1 ? s0 : s1, 8);
        bq += __shfl_xor_sync(0xffffffffu, p1 ? s2 : s3, 8);
        float r = p2 ? bq : a;
        r += __shfl_xor_sync(0xffffffffu, p2 ? a : bq, 16);
        *outp = __float2bfloat16_rn(r + resid);
        if (cta == 0 && lane == 0) st_rlx(&g_epoch, *epoch_s + 1u);
    }
}

typedef CUresult (*EncodeFn)(CUtensorMap*, CUtensorMapDataType, cuuint32_t, void*, const cuuint64_t*, const cuuint64_t*,
                             const cuuint32_t*, const cuuint32_t*, CUtensorMapInterleave, CUtensorMapSwizzle,
                             CUtensorMapL2promotion, CUtensorMapFloatOOBfill);

void encode(EncodeFn fn, CUtensorMap* m, const void* p, int rank, const cuuint64_t* dims, const cuuint64_t* strides,
            const cuuint32_t* box, CUtensorMapSwizzle sw,
            CUtensorMapL2promotion promo = CU_TENSOR_MAP_L2_PROMOTION_L2_256B) {
    const cuuint32_t es[3] = {1, 1, 1};
    fn(m, CU_TENSOR_MAP_DATA_TYPE_BFLOAT16, rank, const_cast<void*>(p), dims, strides, box, es,
       CU_TENSOR_MAP_INTERLEAVE_NONE, sw, promo, CU_TENSOR_MAP_FLOAT_OOB_FILL_NONE);
}

}

extern "C" void kernel_launch(void* const* d_in, const int* in_sizes, int n_in, void* d_out, int out_size) {
    (void)in_sizes; (void)n_in; (void)out_size;
    static EncodeFn fn = nullptr;
    if (!fn) {
        cudaDriverEntryPointQueryResult qr;
        cudaGetDriverEntryPoint("cuTensorMapEncodeTiled", (void**)&fn, cudaEnableDefault, &qr);
        cudaFuncSetAttribute(fused_decode_kernel, cudaFuncAttributeMaxDynamicSharedMemorySize, SMEM_BYTES);
        cudaFuncSetAttribute(fused_decode_kernel, cudaFuncAttributeNonPortableClusterSizeAllowed, 1);
    }
    Maps m;
    {
        const cuuint64_t d[3] = {64, 64ull * 4096, 2}, s[2] = {256, 128};
        const cuuint32_t bx[3] = {64, 64, 2};
        encode(fn, &m.k, d_in[1], 3, d, s, bx, CU_TENSOR_MAP_SWIZZLE_128B);
        encode(fn, &m.v, d_in[2], 3, d, s, bx, CU_TENSOR_MAP_SWIZZLE_128B);
    }
    { const cuuint64_t d[3] = {64, 8, 8}, s[2] = {1024, 128}; const cuuint32_t bx[3] = {64, 8, 8};
      encode(fn, &m.x, d_in[0], 3, d, s, bx, CU_TENSOR_MAP_SWIZZLE_128B); }
    { const cuuint64_t d[2] = {4096, 512}, s[1] = {8192}; const cuuint32_t bx[2] = {32, 256};
      encode(fn, &m.wq, d_in[3], 2, d, s, bx, CU_TENSOR_MAP_SWIZZLE_64B); }
    { const cuuint64_t d[2] = {512, 4096}, s[1] = {1024}; const cuuint32_t bx[2] = {64, 128};
      encode(fn, &m.wo, d_in[4], 2, d, s, bx, CU_TENSOR_MAP_SWIZZLE_128B, CU_TENSOR_MAP_L2_PROMOTION_L2_128B); }
    { const cuuint64_t d[2] = {1792, 512}, s[1] = {3584}; const cuuint32_t bx[2] = {16, 256};
      encode(fn, &m.w1, d_in[6], 2, d, s, bx, CU_TENSOR_MAP_SWIZZLE_32B); }
    { const cuuint64_t d[2] = {512, 1792}, s[1] = {1024}; const cuuint32_t bx[2] = {64, 112};
      encode(fn, &m.w2, d_in[7], 2, d, s, bx, CU_TENSOR_MAP_SWIZZLE_128B, CU_TENSOR_MAP_L2_PROMOTION_L2_128B); }

    cudaLaunchConfig_t cfg = {};
    cfg.gridDim = dim3(NCTA); cfg.blockDim = dim3(NTHREADS); cfg.dynamicSmemBytes = SMEM_BYTES;
    cfg.stream = cudaStreamPerThread;
    cudaLaunchAttribute at[2];
    at[0].id = cudaLaunchAttributeClusterDimension;
    at[0].val.clusterDim.x = CLUSTER; at[0].val.clusterDim.y = 1; at[0].val.clusterDim.z = 1;
    at[1].id = cudaLaunchAttributeClusterSchedulingPolicyPreference;
    at[1].val.clusterSchedulingPolicyPreference = cudaClusterSchedulingPolicyLoadBalancing;
    cfg.attrs = at; cfg.numAttrs = 2;
    cudaLaunchKernelEx(&cfg, fused_decode_kernel, m, (const char*)d_in[3], (__nv_bfloat16*)d_out);
}
```

```cpp
#include <cuda_runtime.h>
#include <cuda_bf16.h>
#include <cuda.h>
#include <stdint.h>

namespace {

constexpr int NCTA = 128;
constexpr int CLUSTER = 16;
constexpr int NTHREADS = 288;
constexpr int CHUNK = 16384;
constexpr int NSLOT = 6;
constexpr int NCHUNK = 22;
constexpr int C_K = 3, C_V = 11, C_W2 = 19, C_WO = 20;
constexpr int DEPTH = 4;
__host__ __device__ constexpr int clk_count(int j) { return j == 18 ? 14 : j == 15 ? 15 : 12; }
constexpr int PF_BYTES = 8192;

constexpr int RED_PITCH = 36;
constexpr int OFF_U = NSLOT * CHUNK;
constexpr int OFF_X = OFF_U;
constexpr int OFF_RED = OFF_U;
constexpr int OFF_P = OFF_U;
constexpr int OFF_OB = OFF_U + 4096;
constexpr int OFF_RIN = OFF_U + 9216;
constexpr int OFF_Q = OFF_RIN + 4096;
constexpr int OFF_OST = OFF_Q;
constexpr int OFF_H = OFF_Q + 1024;
constexpr int OFF_ML = OFF_H + 2176;
constexpr int OFF_STAT = OFF_ML + 32;
constexpr int OFF_BAR = OFF_STAT + 336;
constexpr int SMEM_BYTES = OFF_BAR + 49 * 8;
static_assert(2 * (SMEM_BYTES + 1024) <= 233472, "two CTAs per SM");

struct Maps { CUtensorMap wq, x, w1, k, v, w2, wo; };

__device__ unsigned int g_epoch;
__device__ __align__(128) uint32_t g_o[2 * 8 * 32 * 64];
__device__ __align__(128) uint32_t g_h[8 * 896];

constexpr uint32_t BAR_LIMIT = 1u << 20, POLL_LIMIT = 1u << 23;

__device__ __forceinline__ uint32_t smem_u32(const void* p) { return (uint32_t)__cvta_generic_to_shared(p); }
__device__ __forceinline__ void mbar_init(uint32_t bar, uint32_t cnt) {
    asm volatile("mbarrier.init.shared::cta.b64 [%0], %1;" :: "r"(bar), "r"(cnt) : "memory");
}
__device__ __forceinline__ void mbar_expect(uint32_t bar, uint32_t bytes) {
    asm volatile("mbarrier.arrive.expect_tx.shared::cta.b64 _, [%0], %1;" :: "r"(bar), "r"(bytes) : "memory");
}
__device__ __forceinline__ void mbar_arrive(uint32_t bar) {
    asm volatile("mbarrier.arrive.shared::cta.b64 _, [%0];" :: "r"(bar) : "memory");
}
template <int PHASE = 0>
__device__ __forceinline__ bool mbar_try(uint32_t bar) {
    uint32_t done;
    asm volatile("{\n.reg .pred p;\nmbarrier.try_wait.parity.shared::cta.b64 p, [%1], %2;\nselp.u32 %0, 1, 0, p;\n}"
                 : "=r"(done) : "r"(bar), "n"(PHASE) : "memory");
    return done;
}
__device__ __forceinline__ bool mbar_test(uint32_t bar) {
    uint32_t done;
    asm volatile("{\n.reg .pred p;\nmbarrier.test_wait.parity.shared::cta.b64 p, [%1], 0;\nselp.u32 %0, 1, 0, p;\n}"
                 : "=r"(done) : "r"(bar) : "memory");
    return done;
}
__device__ __forceinline__ void mbar_wait(uint32_t bar) {
    for (uint32_t n = 0; !mbar_try(bar); ) if (++n > BAR_LIMIT) __trap();
}
__device__ __forceinline__ bool mbar_try_cluster(uint32_t bar) {
    uint32_t done;
    asm volatile("{\n.reg .pred p;\nmbarrier.try_wait.parity.acquire.cluster.shared::cta.b64 p, [%1], 0;\nselp.u32 %0, 1, 0, p;\n}"
                 : "=r"(done) : "r"(bar) : "memory");
    return done;
}
__device__ __forceinline__ void mbar_wait_cluster(uint32_t bar) {
    for (uint32_t n = 0; !mbar_try_cluster(bar); ) if (++n > BAR_LIMIT) __trap();
}
__device__ __forceinline__ uint32_t mapa(uint32_t addr, uint32_t rank) {
    uint32_t r; asm("mapa.shared::cluster.u32 %0, %1, %2;" : "=r"(r) : "r"(addr), "r"(rank)); return r;
}
__device__ __forceinline__ void tick_remote(uint32_t bar) {
    asm volatile("mbarrier.arrive.relaxed.cluster.shared::cluster.b64 _, [%0];" :: "r"(bar) : "memory");
}
__device__ __forceinline__ void st_async2(uint32_t dst, uint32_t a, uint32_t b, uint32_t bar) {
    asm volatile("st.async.weak.shared::cluster.mbarrier::complete_tx::bytes.v2.b32 [%0], {%1,%2}, [%3];"
                 :: "r"(dst), "r"(a), "r"(b), "r"(bar) : "memory");
}
__device__ __forceinline__ void st_async4(uint32_t dst, uint32_t a, uint32_t b, uint32_t c, uint32_t d, uint32_t bar) {
    asm volatile("st.async.weak.shared::cluster.mbarrier::complete_tx::bytes.v4.b32 [%0], {%1,%2,%3,%4}, [%5];"
                 :: "r"(dst), "r"(a), "r"(b), "r"(c), "r"(d), "r"(bar) : "memory");
}
__device__ __forceinline__ void tma2d(uint32_t dst, const CUtensorMap* m, int c0, int c1, uint32_t bar) {
    asm volatile("cp.async.bulk.tensor.2d.shared::cluster.global.mbarrier::complete_tx::bytes [%0], [%1, {%3, %4}], [%2];"
                 :: "r"(dst), "l"(m), "r"(bar), "r"(c0), "r"(c1) : "memory");
}
__device__ __forceinline__ void tma3d(uint32_t dst, const CUtensorMap* m, int c0, int c1, int c2, uint32_t bar) {
    asm volatile("cp.async.bulk.tensor.3d.shared::cluster.global.mbarrier::complete_tx::bytes [%0], [%1, {%3, %4, %5}], [%2];"
                 :: "r"(dst), "l"(m), "r"(bar), "r"(c0), "r"(c1), "r"(c2) : "memory");
}
__device__ __forceinline__ void l2_prefetch(const void* src, uint32_t bytes) {
    asm volatile("cp.async.bulk.prefetch.L2.global [%0], %1;" :: "l"(src), "r"(bytes) : "memory");
}
__device__ __forceinline__ void ldsm4(uint32_t (&r)[4], uint32_t addr) {
    asm volatile("ldmatrix.sync.aligned.m8n8.x4.shared.b16 {%0,%1,%2,%3}, [%4];"
                 : "=r"(r[0]), "=r"(r[1]), "=r"(r[2]), "=r"(r[3]) : "r"(addr) : "memory");
}
__device__ __forceinline__ void ldsm4t(uint32_t (&r)[4], uint32_t addr) {
    asm volatile("ldmatrix.sync.aligned.m8n8.x4.trans.shared.b16 {%0,%1,%2,%3}, [%4];"
                 : "=r"(r[0]), "=r"(r[1]), "=r"(r[2]), "=r"(r[3]) : "r"(addr) : "memory");
}
__device__ __forceinline__ void mma16816(float (&d)[4], const uint32_t (&a)[4], uint32_t b0, uint32_t b1) {
    asm volatile("mma.sync.aligned.m16n8k16.row.col.f32.bf16.bf16.f32 {%0,%1,%2,%3}, {%4,%5,%6,%7}, {%8,%9}, {%0,%1,%2,%3};"
                 : "+f"(d[0]), "+f"(d[1]), "+f"(d[2]), "+f"(d[3])
                 : "r"(a[0]), "r"(a[1]), "r"(a[2]), "r"(a[3]), "r"(b0), "r"(b1));
}
__device__ __forceinline__ uint32_t movtrans(uint32_t a) {
    uint32_t d;
    asm volatile("movmatrix.sync.aligned.m8n8.trans.b16 %0, %1;" : "=r"(d) : "r"(a));
    return d;
}
__device__ __forceinline__ uint32_t pack_bf16(float lo, float hi) {
    uint32_t d;
    asm("cvt.rn.bf16x2.f32 %0, %1, %2;" : "=r"(d) : "f"(hi), "f"(lo));
    return d;
}
__device__ __forceinline__ float bf16r(float x) { return __bfloat162float(__float2bfloat16_rn(x)); }
__device__ __forceinline__ float bf_lo(uint32_t u) { return __uint_as_float(u << 16); }
__device__ __forceinline__ float bf_hi(uint32_t u) { return __uint_as_float(u & 0xffff0000u); }
__device__ __forceinline__ uint32_t hadd2_bf16(uint32_t a, uint32_t b) {
    uint32_t d;
    asm("add.rn.bf16x2 %0, %1, %2;" : "=r"(d) : "r"(a), "r"(b));
    return d;
}
__device__ __forceinline__ uint32_t ld_rlx(const uint32_t* p) {
    uint32_t v; asm volatile("ld.relaxed.gpu.global.u32 %0, [%1];" : "=r"(v) : "l"(p) : "memory"); return v;
}
__device__ __forceinline__ void st_rlx(uint32_t* p, uint32_t v) {
    asm volatile("st.relaxed.gpu.global.u32 [%0], %1;" :: "l"(p), "r"(v) : "memory");
}
__device__ __forceinline__ uint4 ld_rlx_2x64(const void* p) {
    unsigned long long a, b;
    asm volatile("ld.relaxed.gpu.global.v2.b64 {%0,%1}, [%2];" : "=l"(a), "=l"(b) : "l"(p) : "memory");
    return make_uint4((uint32_t)a, (uint32_t)(a >> 32), (uint32_t)b, (uint32_t)(b >> 32));
}
__device__ __forceinline__ void st_rlx_2x64(void* p, const uint4& v) {
    asm volatile("st.relaxed.gpu.global.v2.b64 [%0], {%1,%2};" :: "l"(p),
                 "l"(((unsigned long long)v.y << 32) | v.x), "l"(((unsigned long long)v.w << 32) | v.z) : "memory");
}
__device__ __forceinline__ void st_rlx_64(void* p, uint32_t lo, uint32_t hi) {
    asm volatile("st.relaxed.gpu.global.b64 [%0], %1;" :: "l"(p), "l"(((unsigned long long)hi << 32) | lo) : "memory");
}
__device__ __forceinline__ bool tagged(const uint4& v, uint32_t tag) { return (((v.x ^ tag) | (v.z ^ tag)) & 1u) == 0u; }
__device__ __forceinline__ void sts128(uint32_t a, uint32_t x, uint32_t y, uint32_t z, uint32_t w) {
    asm volatile("st.shared.v4.b32 [%0], {%1,%2,%3,%4};" :: "r"(a), "r"(x), "r"(y), "r"(z), "r"(w) : "memory");
}
template <typename T> __device__ __forceinline__ void pin64(T*& p) { asm volatile("" : "+l"(p)); }
__device__ __forceinline__ void pin32(uint32_t& v) { asm volatile("" : "+r"(v)); }
__device__ __forceinline__ void cbar() { asm volatile("bar.sync 1, 256;" ::: "memory"); }
__device__ __forceinline__ float ex2(float x) { float y; asm("ex2.approx.ftz.f32 %0, %1;" : "=f"(y) : "f"(x)); return y; }

__global__ void __launch_bounds__(NTHREADS, 2)
fused_decode_kernel(const char* __restrict__ wq_raw, __nv_bfloat16* __restrict__ out, const __grid_constant__ Maps maps)
{
    extern __shared__ __align__(1024) char smp[];
    const uint32_t sm = smem_u32(smp);
    const int tid = threadIdx.x, warp = tid >> 5, lane = tid & 31;
    const int cta = blockIdx.x, g = cta >> 4, c = cta & 15, b = c >> 1, half = c & 1;
    const bool ffn = g < 7;
    const uint32_t bar_full = sm + OFF_BAR, bar_empty = bar_full + NCHUNK * 8;
    const uint32_t bar_q = bar_empty + 16 * 8, bar_ml = bar_q + 8, bar_r = bar_q + 16, bar_x = bar_q + 24, bar_go = bar_q + 32;
    const uint32_t bar_clk = bar_q + 40 - 13 * 8;

    if (warp == 8) {
        if (lane == 0) {
            mbar_init(bar_x, 1); mbar_init(bar_full, 1); mbar_init(bar_full + 8, 1); mbar_init(bar_full + 16, 1);
            asm volatile("fence.proxy.async.shared::cta;" ::: "memory");
            mbar_expect(bar_full, CHUNK); tma2d(sm, &maps.wq, cta * 32, 0, bar_full);
            mbar_expect(bar_x, 8192); tma3d(sm + OFF_X, &maps.x, 0, 0, 0, bar_x);
            mbar_expect(bar_full + 8, CHUNK); tma2d(sm + CHUNK, &maps.wq, cta * 32, 256, bar_full + 8);
            if (ffn) {
                mbar_expect(bar_full + 16, CHUNK);
                tma2d(sm + 2 * CHUNK, &maps.w1, cta * 16, 0, bar_full + 16);
                tma2d(sm + 2 * CHUNK + 8192, &maps.w1, cta * 16, 256, bar_full + 16);
            } else mbar_arrive(bar_full + 16);
            if (sm & 1023u) __trap();
            #pragma unroll
            for (int s = C_K; s < NCHUNK; s++) mbar_init(bar_full + s * 8, 1);
            #pragma unroll
            for (int s = 0; s < 16; s++) mbar_init(bar_empty + s * 8, (s < 2 || (s >= C_K && s < C_V)) ? 4 : 8);
            mbar_init(bar_q, 1); mbar_init(bar_ml, 1); mbar_init(bar_r, 1); mbar_init(bar_go, 1);
            #pragma unroll
            for (int s = 13; s < C_W2; s++) mbar_init(bar_clk + s * 8, clk_count(s));
            mbar_expect(bar_q, 1024); mbar_expect(bar_ml, 32); mbar_expect(bar_r, 4096);
            asm volatile("fence.mbarrier_init.release.cluster;" ::: "memory");
            asm volatile("fence.proxy.async.shared::cta;" ::: "memory");
        }
        __syncwarp();
        asm volatile("barrier.cluster.arrive.relaxed.aligned;" ::: "memory");
        asm volatile("bar.arrive 2, %0;" :: "n"(NTHREADS) : "memory");
        if (lane == 0) {
            const int row0 = (b * 8 + g) * 4096 + 3072 + half * 512;
            uint32_t dst = sm + C_K * CHUNK;
            #pragma unroll 1
            for (int ch = C_K; ch < NCHUNK; ch++) {
                if (ch >= 17) mbar_wait(bar_clk + (ch < C_W2 ? ch - 4 : ch - 3) * 8);
                else if (ch >= DEPTH) mbar_wait(bar_full + (ch - DEPTH) * 8);
                if (ch >= NSLOT) mbar_wait(bar_empty + (ch - NSLOT) * 8);
                const uint32_t bar = bar_full + ch * 8;
                if (ch < C_W2) {
                    mbar_expect(bar, CHUNK);
                    tma3d(dst, ch < C_V ? &maps.k : &maps.v, 0, row0 + ((ch - C_K) & 7) * 64, 0, bar);
                } else {
                    mbar_expect(bar, ch == C_W2 ? 14336 : CHUNK);
                    tma2d(dst, ch == C_W2 ? &maps.w2 : &maps.wo, g * 64,
                          ch == C_W2 ? c * 112 : c * 256 + (ch - C_WO) * 128, bar);
                }
                dst = (dst == sm + (NSLOT - 1) * CHUNK) ? sm : dst + CHUNK;
            }
            mbar_wait(bar_clk + 15 * 8);
            mbar_arrive(bar_go);
            #pragma unroll
            for (int s = 13; s < C_W2; s++)
                asm volatile("mbarrier.arrive.shared::cta.b64 _, [%0], %1;" :: "r"(bar_clk + s * 8), "r"(2 * clk_count(s) - 16) : "memory");
            #pragma unroll
            for (int s = 13; s < C_W2; s++)
                for (uint32_t n = 0; !mbar_try<1>(bar_clk + s * 8); ) if (++n > BAR_LIMIT) __trap();
        }
        __syncwarp();
        asm volatile("barrier.cluster.wait.aligned;" ::: "memory");
        return;
    }

    if (tid == 0) l2_prefetch(wq_raw + (size_t)cta * 32768, PF_BYTES);
    asm volatile("barrier.cluster.arrive.relaxed.aligned;" ::: "memory");
    const int gl = lane >> 2, t = lane & 3;
    float* lnst = reinterpret_cast<float*>(smp + OFF_STAT + 256);
    volatile uint32_t* epoch_s = reinterpret_cast<volatile uint32_t*>(smp + OFF_STAT + 320);
    const int ru = lane & 7, rp = lane >> 3;
    const int ob = 2 * (ru & 3) + (rp & 1);
    const int ocol = g * 64 + (c >> 2) * 16 + 2 * (c & 3) + (ru >> 2) + 8 * (rp >> 1);
    uint32_t epoch_r = 0;
    if (tid == 64) epoch_r = ld_rlx(&g_epoch);
    asm volatile("bar.sync 2, %0;" :: "n"(NTHREADS) : "memory");
    if (tid == 64) *epoch_s = epoch_r;
    mbar_wait(bar_x);
    uint32_t xf[8];
    #pragma unroll
    for (int j = 0; j < 8; j++)
        xf[j] = *reinterpret_cast<const uint32_t*>(smp + OFF_X + warp * 1024 + gl * 128 + ((j ^ gl) << 4) + t * 4);
    const float resid = __bfloat162float(*reinterpret_cast<const __nv_bfloat16*>(
        smp + OFF_X + g * 1024 + ob * 128 + ((((ocol >> 3) & 7) ^ ob) << 4) + (ocol & 7) * 2));
    {
        const char* xr = smp + OFF_X + (lane >> 3) * 1024 + warp * 128 + (lane & 7) * 16;
        const uint4 xa = *reinterpret_cast<const uint4*>(xr), xb = *reinterpret_cast<const uint4*>(xr + 4096);
        const float sh = bf_lo(*reinterpret_cast<const uint32_t*>(smp + OFF_X + warp * 128));
        const uint32_t w[8] = {xa.x, xa.y, xa.z, xa.w, xb.x, xb.y, xb.z, xb.w};
        float s4[4] = {}, q4[4] = {};
        #pragma unroll
        for (int j = 0; j < 8; j++) {
            const float lo = bf_lo(w[j]) - sh, hi = bf_hi(w[j]) - sh;
            s4[j & 3] += lo + hi;
            q4[j & 3] = fmaf(lo, lo, fmaf(hi, hi, q4[j & 3]));
        }
        float s = (s4[0] + s4[1]) + (s4[2] + s4[3]), q2 = (q4[0] + q4[1]) + (q4[2] + q4[3]);
        #pragma unroll
        for (int o = 16; o > 0; o >>= 1) {
            s += __shfl_xor_sync(0xffffffffu, s, o);
            q2 += __shfl_xor_sync(0xffffffffu, q2, o);
        }
        const float ms = s * (1.f / 512.f), mean = sh + ms;
        q2 = fmaxf(fmaf(-ms, s, q2), 0.f);
        const float den = bf16r(__fsqrt_rn(bf16r(bf16r(q2 * (1.f / 512.f)) + 1e-5f)));
        if (lane == 0) *reinterpret_cast<float2*>(lnst + warp * 2) = make_float2(bf16r(mean), __frcp_rn(den));
    }
    cbar();
    {
        const float2 st = *reinterpret_cast<const float2*>(lnst + gl * 2);
        #pragma unroll
        for (int j = 0; j < 8; j++)
            xf[j] = pack_bf16(bf16r(bf_lo(xf[j]) - st.x) * st.y, bf16r(bf_hi(xf[j]) - st.x) * st.y);
    }
    const uint32_t tag = (*epoch_s + 1u) & 1u;

    float* red = reinterpret_cast<float*>(smp + OFF_RED);
    const int mj = lane >> 3, mr = lane & 7;
    float* r0 = red + (warp * 8 + 2 * t) * RED_PITCH + gl;
    {
        float aq[2][4] = {};
        mbar_wait(bar_full + (warp >> 2) * 8);
        const uint32_t wqs = sm + (warp >> 2) * CHUNK;
        #pragma unroll
        for (int s = 0; s < 4; s++) {
            const int row = (warp & 3) * 64 + s * 16 + (mj >> 1) * 8 + mr;
            #pragma unroll
            for (int j = 0; j < 2; j++) {
                uint32_t a[4];
                ldsm4t(a, wqs + row * 64 + (((2 * j + (mj & 1)) ^ ((row >> 1) & 3)) << 4));
                mma16816(aq[j], a, xf[2 * s], xf[2 * s + 1]);
            }
        }
        __syncwarp();
        if (lane == 0) mbar_arrive(bar_empty + (warp >> 2) * 8);
        #pragma unroll
        for (int j = 0; j < 2; j++) {
            r0[j * 16] = aq[j][0]; r0[RED_PITCH + j * 16] = aq[j][1];
            r0[j * 16 + 8] = aq[j][2]; r0[RED_PITCH + j * 16 + 8] = aq[j][3];
        }
    }
    cbar();
    asm volatile("barrier.cluster.wait.aligned;" ::: "memory");
    if (warp < 4) {
        const int bb = tid >> 4, wd = tid & 15;
        const int col = (wd >> 3) * 16 + ((wd >> 1) & 3) * 2 + (wd & 1) * 8;
        float s0 = 0.f, s1 = 0.f;
        #pragma unroll
        for (int w = 0; w < 8; w++) {
            const float2 f = *reinterpret_cast<const float2*>(red + (w * 8 + bb) * RED_PITCH + col);
            s0 += f.x; s1 += f.y;
        }
        const uint32_t u = pack_bf16(s0, s1);
        const int q0 = (lane & 16) + (lane & 3) * 4;
        const uint32_t u0 = __shfl_sync(0xffffffffu, u, q0), u1 = __shfl_sync(0xffffffffu, u, q0 + 1);
        const uint32_t u2 = __shfl_sync(0xffffffffu, u, q0 + 2), u3 = __shfl_sync(0xffffffffu, u, q0 + 3);
        if (wd < 8) {
            const uint32_t rank = 2 * bb + (wd >> 2);
            st_async4(mapa(sm + OFF_Q + c * 64 + (wd & 3) * 16, rank), u0, u1, u2, u3, mapa(bar_q, rank));
        }
    }
    if (ffn) {
        float ah[4] = {};
        mbar_wait(bar_full + 2 * 8);
        const uint32_t w1s = sm + 2 * CHUNK;
        #pragma unroll
        for (int s = 0; s < 4; s++) {
            const int row = warp * 64 + s * 16 + (mj >> 1) * 8 + mr;
            uint32_t a[4];
            ldsm4t(a, w1s + row * 32 + (((mj & 1) ^ ((row >> 2) & 1)) << 4));
            mma16816(ah, a, xf[2 * s], xf[2 * s + 1]);
        }
        __syncwarp();
        if (lane == 0) mbar_arrive(bar_empty + 2 * 8);
        cbar();
        r0[0] = ah[0]; r0[RED_PITCH] = ah[1]; r0[8] = ah[2]; r0[RED_PITCH + 8] = ah[3];
        cbar();
        if (warp >= 6) {
            const int bb = (tid & 63) >> 3, wd = tid & 7;
            float s0 = 0.f, s1 = 0.f;
            #pragma unroll
            for (int w = 0; w < 8; w++) {
                const float2 f = *reinterpret_cast<const float2*>(red + (w * 8 + bb) * RED_PITCH + 2 * wd);
                s0 += f.x; s1 += f.y;
            }
            s0 = bf16r(s0); s1 = bf16r(s1);
            s0 = __fdividef(s0, 1.f + __expf(-s0)); s1 = __fdividef(s1, 1.f + __expf(-s1));
            const uint32_t u = pack_bf16(s0, s1);
            const uint32_t un = __shfl_down_sync(0xffffffffu, u, 1);
            if (!(wd & 1)) st_rlx_64(g_h + bb * 896 + cta * 8 + wd, (u & ~1u) | tag, un);
        }
    } else {
        __syncwarp();
        if (lane == 0) mbar_arrive(bar_empty + 2 * 8);
    }

    float sc[4][4];
    float m0 = -INFINITY, m1 = -INFINITY;
    {
        mbar_wait_cluster(bar_q);
        uint32_t qb[8][2];
        #pragma unroll
        for (int s = 0; s < 8; s++) {
            const uint2 v = *reinterpret_cast<const uint2*>(smp + OFF_Q + (((gl & 3) * 8 + s) * 4 + t) * 8);
            qb[s][0] = v.x; qb[s][1] = v.y;
        }
        const uint32_t koff = ((warp & 3) * 16 + (mj & 1) * 8 + mr) * 128;
        #pragma unroll
        for (int i = 0; i < 4; i++) {
            const int ck = C_K + 2 * i + (warp >> 2);
            mbar_wait(bar_full + ck * 8);
            const uint32_t ks = sm + (ck % NSLOT) * CHUNK + koff;
            float s0[4] = {}, s1[4] = {};
            #pragma unroll
            for (int s = 0; s < 4; s++) {
                const uint32_t sw = ((2 * s + (mj >> 1)) ^ mr) << 4;
                uint32_t a[4], a2[4];
                ldsm4(a, ks + sw);
                ldsm4(a2, ks + 8192 + sw);
                mma16816(s0, a, qb[s][0], qb[s][1]);
                mma16816(s1, a2, qb[4 + s][0], qb[4 + s][1]);
            }
            __syncwarp();
            if (lane == 0) mbar_arrive(bar_empty + ck * 8);
            #pragma unroll
            for (int k = 0; k < 4; k++) sc[i][k] = bf16r(bf16r(s0[k] + s1[k]) * 0.08838834764831845f);
            m0 = fmaxf(m0, fmaxf(sc[i][0], sc[i][2]));
            m1 = fmaxf(m1, fmaxf(sc[i][1], sc[i][3]));
        }
    }
    float* wmax = reinterpret_cast<float*>(smp + OFF_STAT);
    float* wsum = wmax + 32;
    constexpr float L2E = 1.4426950408889634f;
    {
        #pragma unroll
        for (int o = 4; o < 32; o <<= 1) {
            m0 = fmaxf(m0, __shfl_xor_sync(0xffffffffu, m0, o));
            m1 = fmaxf(m1, __shfl_xor_sync(0xffffffffu, m1, o));
        }
        if (lane < 2) *reinterpret_cast<float2*>(wmax + warp * 4 + 2 * lane) = make_float2(m0, m1);
        cbar();
        #pragma unroll
        for (int w = 0; w < 8; w++) {
            const float2 f = *reinterpret_cast<const float2*>(wmax + w * 4 + 2 * (t & 1));
            m0 = fmaxf(m0, f.x); m1 = fmaxf(m1, f.y);
        }
        float l0 = 0.f, l1 = 0.f;
        uint32_t pw[4][2];
        #pragma unroll
        for (int i = 0; i < 4; i++) {
            const float p0 = ex2((sc[i][0] - m0) * L2E), p1 = ex2((sc[i][1] - m1) * L2E);
            const float p2 = ex2((sc[i][2] - m0) * L2E), p3 = ex2((sc[i][3] - m1) * L2E);
            l0 += p0 + p2; l1 += p1 + p3;
            pw[i][0] = movtrans(pack_bf16(p0, p1));
            pw[i][1] = movtrans(pack_bf16(p2, p3));
        }
        if (lane < 16) {
            char* pd = smp + OFF_P + ((warp >> 2) * 2 + ((warp >> 1) & 1)) * 256 + lane * 16 + (warp & 1) * 8;
            #pragma unroll
            for (int i = 0; i < 4; i++) *reinterpret_cast<uint2*>(pd + i * 1024) = make_uint2(pw[i][0], pw[i][1]);
        }
        #pragma unroll
        for (int o = 4; o < 32; o <<= 1) {
            l0 += __shfl_xor_sync(0xffffffffu, l0, o);
            l1 += __shfl_xor_sync(0xffffffffu, l1, o);
        }
        if (lane < 2) *reinterpret_cast<float2*>(wsum + warp * 4 + 2 * lane) = make_float2(l0, l1);
    }
    cbar();
    float l0 = 0.f, l1 = 0.f;
    #pragma unroll
    for (int w = 0; w < 8; w++) {
        const float2 f = *reinterpret_cast<const float2*>(wsum + w * 4 + 2 * (t & 1));
        l0 += f.x; l1 += f.y;
    }
    if (tid < 2) {
        const uint32_t dst = mapa(sm + OFF_ML + tid * 8, c ^ 1), bar = mapa(bar_ml, c ^ 1);
        st_async2(dst, __float_as_uint(m0), __float_as_uint(m1), bar);
        st_async2(dst + 16, __float_as_uint(l0), __float_as_uint(l1), bar);
    }

    const uint32_t* op = g_o + (((tid >> 4) & 7) * 32 + 2 * c + (tid >> 7)) * 64 + (tid & 15) * 4;
    uint32_t* opub = g_o + ((half * 8 + b) * 32 + g * 4) * 64 + (tid & 63) * 4;
    __nv_bfloat16* outp = out + ob * 512 + ocol;
    uint32_t s_ost = sm + OFF_OST + gl * 256 + (t * 4 + ((warp >> 1) ^ (t & 2))) * 16 + (warp & 1) * 8;
    uint32_t s_rdst = mapa(sm + OFF_RIN + (c * 2 + (warp >> 2)) * 128 + ru * 16, (warp & 3) * 4 + rp);
    uint32_t s_rbar = mapa(bar_r, (warp & 3) * 4 + rp);
    uint32_t s_obw = sm + OFF_OB + (tid >> 4) * 320 + (((tid & 15) ^ ((tid >> 4) & 1)) << 4);
    uint32_t s_obr = sm + OFF_OB + gl * 320 + t * 64 + ((((warp >> 2) * 2) ^ (t & 2) ^ (gl & 1)) << 4);
    const int hb = min(tid / 14, 7), hpc = tid - (tid / 14) * 14;
    const uint32_t* hp = g_h + hb * 896 + c * 56 + hpc * 4;
    uint32_t s_h = sm + OFF_H + hb * 272 + hpc * 16;
    pin64(op); pin64(opub); pin64(outp); pin64(hp);
    uint32_t aoff = sm + (warp >> 2) * 8192 + ((mj >> 1) * 8 + mr) * 128 + (((2 * (warp & 3) + (mj & 1)) ^ mr) << 4);
    uint32_t s_hs = sm + OFF_H + (gl * 68 + (warp >> 2) * 32 + t) * 4;
    uint32_t s_rin = sm + OFF_RIN + lane * 16;
    uint32_t ptid = tid;
    uint32_t s_clk = mapa(bar_clk + C_V * 8, tid & 15);
    pin32(s_ost); pin32(s_rdst); pin32(s_rbar); pin32(s_obw); pin32(s_obr); pin32(s_h);
    pin32(aoff); pin32(s_hs); pin32(s_rin); pin32(ptid); pin32(s_clk);
    uint4 hv = make_uint4(tag, 0u, tag, 0u);
    if (tid < 112) hv = ld_rlx_2x64(hp);
    if (tid < 64) st_rlx_2x64(opub, make_uint4(tag ^ 1u, 0u, tag ^ 1u, 0u));

    float f0 = 0.f, f1 = 0.f;
    float oc[4][4] = {};
    {
        const int ach = 2 * warp + (mj & 1);
        uint32_t voff = (ach >> 3) * 8192 + ((mj >> 1) * 8 + mr) * 128 + (((ach & 7) ^ mr) << 4);
        pin32(voff);
        const uint4* pfp = reinterpret_cast<const uint4*>(smp + OFF_P) + (lane & 15);
        uint32_t vs = sm + (C_V % NSLOT) * CHUNK;
        #pragma unroll 1
        for (int j = 0; j < 8; j++) {
            const uint4 pa = pfp[j * 32], pb = pfp[j * 32 + 16];
            if (j == 6) {
                for (uint32_t n = 0; !tagged(hv, tag); ) {
                    hv = ld_rlx_2x64(hp);
                    if (++n > POLL_LIMIT) __trap();
                }
                if (tid < 112) sts128(s_h, hv.x, hv.y, hv.z, hv.w);
                __syncwarp();
                mbar_wait_cluster(bar_ml);
                const float* pm = reinterpret_cast<const float*>(smp + OFF_ML) + (t & 1) * 2;
                const float mo0 = pm[0], mo1 = pm[1];
                const float mt0 = fmaxf(m0, mo0), mt1 = fmaxf(m1, mo1);
                const float e0 = ex2((m0 - mt0) * L2E), e1 = ex2((m1 - mt1) * L2E);
                f0 = __fdividef(e0, l0 * e0 + pm[4] * ex2((mo0 - mt0) * L2E));
                f1 = __fdividef(e1, l1 * e1 + pm[5] * ex2((mo1 - mt1) * L2E));
            }
            mbar_wait(bar_full + (C_V + j) * 8);
            if (j >= 2 && j != 4 && ptid >= 240) tick_remote(s_clk + j * 8);
            uint32_t a[4][4];
            #pragma unroll
            for (int s = 0; s < 4; s++) ldsm4t(a[s], vs + voff + s * 2048);
            mma16816(oc[0], a[0], pa.x, pa.y);
            mma16816(oc[1], a[1], pa.z, pa.w);
            mma16816(oc[2], a[2], pb.x, pb.y);
            mma16816(oc[3], a[3], pb.z, pb.w);
            __syncwarp();
            if (j < 5 && lane == 0) mbar_arrive(bar_empty + (C_V + j) * 8);
            vs = (vs == sm + (NSLOT - 1) * CHUNK) ? sm : vs + CHUNK;
        }
    }
    {
        const float o0 = (oc[0][0] + oc[1][0]) + (oc[2][0] + oc[3][0]);
        const float o1 = (oc[0][1] + oc[1][1]) + (oc[2][1] + oc[3][1]);
        const float o2 = (oc[0][2] + oc[1][2]) + (oc[2][2] + oc[3][2]);
        const float o3 = (oc[0][3] + oc[1][3]) + (oc[2][3] + oc[3][3]);
        const uint32_t u0 = movtrans(pack_bf16(o0 * f0, o1 * f1));
        const uint32_t u1 = movtrans(pack_bf16(o2 * f0, o3 * f1));
        if (!(ptid & 16))
            asm volatile("st.shared.v2.b32 [%0], {%1,%2};" :: "r"(s_ost), "r"((u0 & ~1u) | tag), "r"(u1) : "memory");
        cbar();
        if (ptid < 64) st_rlx_2x64(opub, *reinterpret_cast<const uint4*>(smp + OFF_OST + ptid * 16));
        if (ptid >= 240) tick_remote(s_clk + 4 * 8);
    }

    {
        float ac[4][4] = {};
        mbar_wait(bar_full + C_W2 * 8);
        #pragma unroll
        for (int s = 0; s < 4; s++) {
            if (s < 3 || ptid < 128) {
                uint32_t a[4], h0, h1;
                ldsm4t(a, aoff + (C_W2 % NSLOT) * CHUNK + s * 2048);
                asm volatile("ld.shared.b32 %0, [%1];" : "=r"(h0) : "r"(s_hs + s * 32) : "memory");
                asm volatile("ld.shared.b32 %0, [%1];" : "=r"(h1) : "r"(s_hs + s * 32 + 16) : "memory");
                mma16816(ac[s], a, h0, h1);
            }
        }
        mbar_wait(bar_go);
        uint4 oa = ld_rlx_2x64(op), obv = ld_rlx_2x64(op + 16384);
        uint32_t wa[8][4];
        bool have0 = false, have1 = false;
        auto wo_part = [&](int i) {
            #pragma unroll
            for (int s = 0; s < 4; s++) ldsm4t(wa[i * 4 + s], aoff + (C_WO % NSLOT + i) * CHUNK + s * 2048);
        };
        for (uint32_t n = 0; ; ) {
            if (!have0 && __all_sync(0xffffffffu, mbar_test(bar_full + C_WO * 8))) { have0 = true; wo_part(0); }
            if (!have1 && __all_sync(0xffffffffu, mbar_test(bar_full + (C_WO + 1) * 8))) { have1 = true; wo_part(1); }
            if (++n > POLL_LIMIT) __trap();
            const bool na = !tagged(oa, tag), nb = !tagged(obv, tag);
            if (!__any_sync(0xffffffffu, na || nb)) break;
            if (na) oa = ld_rlx_2x64(op);
            if (nb) obv = ld_rlx_2x64(op + 16384);
        }
        sts128(s_obw, hadd2_bf16(oa.x, obv.x), hadd2_bf16(oa.y, obv.y), hadd2_bf16(oa.z, obv.z), hadd2_bf16(oa.w, obv.w));
        cbar();
        uint4 of[4];
        #pragma unroll
        for (int i = 0; i < 4; i++)
            asm volatile("ld.shared.v4.b32 {%0,%1,%2,%3}, [%4];" : "=r"(of[i].x), "=r"(of[i].y), "=r"(of[i].z), "=r"(of[i].w)
                         : "r"((s_obr ^ ((i & 1) << 4)) + (i >> 1) * 2560) : "memory");
        if (!have0) { mbar_wait(bar_full + C_WO * 8); wo_part(0); }
        mma16816(ac[0], wa[0], of[0].x, of[0].y);
        mma16816(ac[1], wa[1], of[0].z, of[0].w);
        mma16816(ac[2], wa[2], of[1].x, of[1].y);
        mma16816(ac[3], wa[3], of[1].z, of[1].w);
        if (!have1) { mbar_wait(bar_full + (C_WO + 1) * 8); wo_part(1); }
        mma16816(ac[0], wa[4], of[2].x, of[2].y);
        mma16816(ac[1], wa[5], of[2].z, of[2].w);
        mma16816(ac[2], wa[6], of[3].x, of[3].y);
        mma16816(ac[3], wa[7], of[3].z, of[3].w);
        st_async4(s_rdst,
                  __float_as_uint((ac[0][0] + ac[1][0]) + (ac[2][0] + ac[3][0])),
                  __float_as_uint((ac[0][1] + ac[1][1]) + (ac[2][1] + ac[3][1])),
                  __float_as_uint((ac[0][2] + ac[1][2]) + (ac[2][2] + ac[3][2])),
                  __float_as_uint((ac[0][3] + ac[1][3]) + (ac[2][3] + ac[3][3])), s_rbar);
    }

    if (ptid < 32) {
        mbar_wait_cluster(bar_r);
        float4 v[8];
        #pragma unroll
        for (int i = 0; i < 8; i++)
            asm volatile("ld.shared.v4.f32 {%0,%1,%2,%3}, [%4];" : "=f"(v[i].x), "=f"(v[i].y), "=f"(v[i].z), "=f"(v[i].w)
                         : "r"(s_rin + i * 512) : "memory");
        const float s0 = ((v[0].x + v[1].x) + (v[2].x + v[3].x)) + ((v[4].x + v[5].x) + (v[6].x + v[7].x));
        const float s1 = ((v[0].y + v[1].y) + (v[2].y + v[3].y)) + ((v[4].y + v[5].y) + (v[6].y + v[7].y));
        const float s2 = ((v[0].z + v[1].z) + (v[2].z + v[3].z)) + ((v[4].z + v[5].z) + (v[6].z + v[7].z));
        const float s3 = ((v[0].w + v[1].w) + (v[2].w + v[3].w)) + ((v[4].w + v[5].w) + (v[6].w + v[7].w));
        const bool p1 = ptid & 8, p2 = ptid & 16;
        float a = p1 ? s1 : s0, bq = p1 ? s3 : s2;
        a += __shfl_xor_sync(0xffffffffu, p1 ? s0 : s1, 8);
        bq += __shfl_xor_sync(0xffffffffu, p1 ? s2 : s3, 8);
        float r = p2 ? bq : a;
        r += __shfl_xor_sync(0xffffffffu, p2 ? a : bq, 16);
        *outp = __float2bfloat16_rn(r + resid);
        if (cta == 0 && lane == 0) st_rlx(&g_epoch, *epoch_s + 1u);
    }
}

typedef CUresult (*EncodeFn)(CUtensorMap*, CUtensorMapDataType, cuuint32_t, void*, const cuuint64_t*, const cuuint64_t*,
                             const cuuint32_t*, const cuuint32_t*, CUtensorMapInterleave, CUtensorMapSwizzle,
                             CUtensorMapL2promotion, CUtensorMapFloatOOBfill);

void encode(EncodeFn fn, CUtensorMap* m, const void* p, int rank, const cuuint64_t* dims, const cuuint64_t* strides,
            const cuuint32_t* box, CUtensorMapSwizzle sw,
            CUtensorMapL2promotion promo = CU_TENSOR_MAP_L2_PROMOTION_L2_256B) {
    const cuuint32_t es[3] = {1, 1, 1};
    fn(m, CU_TENSOR_MAP_DATA_TYPE_BFLOAT16, rank, const_cast<void*>(p), dims, strides, box, es,
       CU_TENSOR_MAP_INTERLEAVE_NONE, sw, promo, CU_TENSOR_MAP_FLOAT_OOB_FILL_NONE);
}

}

extern "C" void kernel_launch(void* const* d_in, const int* in_sizes, int n_in, void* d_out, int out_size) {
    (void)in_sizes; (void)n_in; (void)out_size;
    static EncodeFn fn = nullptr;
    if (!fn) {
        cudaDriverEntryPointQueryResult qr;
        cudaGetDriverEntryPoint("cuTensorMapEncodeTiled", (void**)&fn, cudaEnableDefault, &qr);
        cudaFuncSetAttribute(fused_decode_kernel, cudaFuncAttributeMaxDynamicSharedMemorySize, SMEM_BYTES);
        cudaFuncSetAttribute(fused_decode_kernel, cudaFuncAttributeNonPortableClusterSizeAllowed, 1);
    }
    Maps m;
    {
        const cuuint64_t d[3] = {64, 64ull * 4096, 2}, s[2] = {256, 128};
        const cuuint32_t bx[3] = {64, 64, 2};
        encode(fn, &m.k, d_in[1], 3, d, s, bx, CU_TENSOR_MAP_SWIZZLE_128B);
        encode(fn, &m.v, d_in[2], 3, d, s, bx, CU_TENSOR_MAP_SWIZZLE_128B);
    }
    { const cuuint64_t d[3] = {64, 8, 8}, s[2] = {1024, 128}; const cuuint32_t bx[3] = {64, 8, 8};
      encode(fn, &m.x, d_in[0], 3, d, s, bx, CU_TENSOR_MAP_SWIZZLE_128B); }
    { const cuuint64_t d[2] = {4096, 512}, s[1] = {8192}; const cuuint32_t bx[2] = {32, 256};
      encode(fn, &m.wq, d_in[3], 2, d, s, bx, CU_TENSOR_MAP_SWIZZLE_64B); }
    { const cuuint64_t d[2] = {512, 4096}, s[1] = {1024}; const cuuint32_t bx[2] = {64, 128};
      encode(fn, &m.wo, d_in[4], 2, d, s, bx, CU_TENSOR_MAP_SWIZZLE_128B, CU_TENSOR_MAP_L2_PROMOTION_L2_128B); }
    { const cuuint64_t d[2] = {1792, 512}, s[1] = {3584}; const cuuint32_t bx[2] = {16, 256};
      encode(fn, &m.w1, d_in[6], 2, d, s, bx, CU_TENSOR_MAP_SWIZZLE_32B); }
    { const cuuint64_t d[2] = {512, 1792}, s[1] = {1024}; const cuuint32_t bx[2] = {64, 112};
      encode(fn, &m.w2, d_in[7], 2, d, s, bx, CU_TENSOR_MAP_SWIZZLE_128B, CU_TENSOR_MAP_L2_PROMOTION_L2_128B); }

    cudaLaunchConfig_t cfg = {};
    cfg.gridDim = dim3(NCTA); cfg.blockDim = dim3(NTHREADS); cfg.dynamicSmemBytes = SMEM_BYTES;
    cfg.stream = cudaStreamPerThread;
    cudaLaunchAttribute at[2];
    at[0].id = cudaLaunchAttributeClusterDimension;
    at[0].val.clusterDim.x = CLUSTER; at[0].val.clusterDim.y = 1; at[0].val.clusterDim.z = 1;
    at[1].id = cudaLaunchAttributeClusterSchedulingPolicyPreference;
    at[1].val.clusterSchedulingPolicyPreference = cudaClusterSchedulingPolicyLoadBalancing;
    cfg.attrs = at; cfg.numAttrs = 2;
    cudaLaunchKernelEx(&cfg, fused_decode_kernel, (const char*)d_in[3], (__nv_bfloat16*)d_out, m);
}
```

```cpp
#include <cuda_runtime.h>
#include <cuda_bf16.h>
#include <cuda.h>
#include <stdint.h>

namespace {

constexpr int NCTA = 128;
constexpr int CLUSTER = 16;
constexpr int NTHREADS = 288;
constexpr int CHUNK = 16384;
constexpr int NSLOT = 6;
constexpr int NCHUNK = 22;
constexpr int C_K = 3, C_V = 11, C_W2 = 19, C_WO = 20;
constexpr int DEPTH = 4;
__host__ __device__ constexpr int clk_count(int j) { return j == 18 ? 14 : j == 15 ? 15 : 12; }
constexpr int PF_BYTES = 8192;

constexpr int RED_PITCH = 36;
constexpr int OFF_U = NSLOT * CHUNK;
constexpr int OFF_X = OFF_U;
constexpr int OFF_RED = OFF_U;
constexpr int OFF_P = OFF_U;
constexpr int OFF_OB = OFF_U + 4096;
constexpr int OFF_RIN = OFF_U + 9216;
constexpr int OFF_Q = OFF_RIN + 4096;
constexpr int OFF_OST = OFF_Q;
constexpr int OFF_H = OFF_Q + 1024;
constexpr int OFF_ML = OFF_H + 2176;
constexpr int OFF_STAT = OFF_ML + 32;
constexpr int OFF_BAR = OFF_STAT + 336;
constexpr int SMEM_BYTES = OFF_BAR + 49 * 8;
static_assert(2 * (SMEM_BYTES + 1024) <= 233472, "two CTAs per SM");

struct Maps { CUtensorMap wq, x, w1, k, v, w2, wo; };

__device__ unsigned int g_epoch;
__device__ __align__(128) uint32_t g_o[2 * 8 * 32 * 64];
__device__ __align__(128) uint32_t g_h[8 * 896 * 2];

constexpr uint32_t BAR_LIMIT = 1u << 20, POLL_LIMIT = 1u << 23;

__device__ __forceinline__ uint32_t smem_u32(const void* p) { return (uint32_t)__cvta_generic_to_shared(p); }
__device__ __forceinline__ void mbar_init(uint32_t bar, uint32_t cnt) {
    asm volatile("mbarrier.init.shared::cta.b64 [%0], %1;" :: "r"(bar), "r"(cnt) : "memory");
}
__device__ __forceinline__ void mbar_expect(uint32_t bar, uint32_t bytes) {
    asm volatile("mbarrier.arrive.expect_tx.shared::cta.b64 _, [%0], %1;" :: "r"(bar), "r"(bytes) : "memory");
}
__device__ __forceinline__ void mbar_arrive(uint32_t bar) {
    asm volatile("mbarrier.arrive.shared::cta.b64 _, [%0];" :: "r"(bar) : "memory");
}
template <int PHASE = 0>
__device__ __forceinline__ bool mbar_try(uint32_t bar) {
    uint32_t done;
    asm volatile("{\n.reg .pred p;\nmbarrier.try_wait.parity.shared::cta.b64 p, [%1], %2;\nselp.u32 %0, 1, 0, p;\n}"
                 : "=r"(done) : "r"(bar), "n"(PHASE) : "memory");
    return done;
}
__device__ __forceinline__ bool mbar_test(uint32_t bar) {
    uint32_t done;
    asm volatile("{\n.reg .pred p;\nmbarrier.test_wait.parity.shared::cta.b64 p, [%1], 0;\nselp.u32 %0, 1, 0, p;\n}"
                 : "=r"(done) : "r"(bar) : "memory");
    return done;
}
__device__ __forceinline__ void mbar_wait(uint32_t bar) {
    for (uint32_t n = 0; !mbar_try(bar); ) if (++n > BAR_LIMIT) __trap();
}
__device__ __forceinline__ bool mbar_try_cluster(uint32_t bar) {
    uint32_t done;
    asm volatile("{\n.reg .pred p;\nmbarrier.try_wait.parity.acquire.cluster.shared::cta.b64 p, [%1], 0;\nselp.u32 %0, 1, 0, p;\n}"
                 : "=r"(done) : "r"(bar) : "memory");
    return done;
}
__device__ __forceinline__ void mbar_wait_cluster(uint32_t bar) {
    for (uint32_t n = 0; !mbar_try_cluster(bar); ) if (++n > BAR_LIMIT) __trap();
}
__device__ __forceinline__ uint32_t mapa(uint32_t addr, uint32_t rank) {
    uint32_t r; asm("mapa.shared::cluster.u32 %0, %1, %2;" : "=r"(r) : "r"(addr), "r"(rank)); return r;
}
__device__ __forceinline__ void tick_remote(uint32_t bar) {
    asm volatile("mbarrier.arrive.relaxed.cluster.shared::cluster.b64 _, [%0];" :: "r"(bar) : "memory");
}
__device__ __forceinline__ void st_async2(uint32_t dst, uint32_t a, uint32_t b, uint32_t bar) {
    asm volatile("st.async.weak.shared::cluster.mbarrier::complete_tx::bytes.v2.b32 [%0], {%1,%2}, [%3];"
                 :: "r"(dst), "r"(a), "r"(b), "r"(bar) : "memory");
}
__device__ __forceinline__ void st_async4(uint32_t dst, uint32_t a, uint32_t b, uint32_t c, uint32_t d, uint32_t bar) {
    asm volatile("st.async.weak.shared::cluster.mbarrier::complete_tx::bytes.v4.b32 [%0], {%1,%2,%3,%4}, [%5];"
                 :: "r"(dst), "r"(a), "r"(b), "r"(c), "r"(d), "r"(bar) : "memory");
}
__device__ __forceinline__ void tma2d(uint32_t dst, const CUtensorMap* m, int c0, int c1, uint32_t bar) {
    asm volatile("cp.async.bulk.tensor.2d.shared::cluster.global.mbarrier::complete_tx::bytes [%0], [%1, {%3, %4}], [%2];"
                 :: "r"(dst), "l"(m), "r"(bar), "r"(c0), "r"(c1) : "memory");
}
__device__ __forceinline__ void tma3d(uint32_t dst, const CUtensorMap* m, int c0, int c1, int c2, uint32_t bar) {
    asm volatile("cp.async.bulk.tensor.3d.shared::cluster.global.mbarrier::complete_tx::bytes [%0], [%1, {%3, %4, %5}], [%2];"
                 :: "r"(dst), "l"(m), "r"(bar), "r"(c0), "r"(c1), "r"(c2) : "memory");
}
__device__ __forceinline__ void l2_prefetch(const void* src, uint32_t bytes) {
    asm volatile("cp.async.bulk.prefetch.L2.global [%0], %1;" :: "l"(src), "r"(bytes) : "memory");
}
__device__ __forceinline__ void ldsm4(uint32_t (&r)[4], uint32_t addr) {
    asm volatile("ldmatrix.sync.aligned.m8n8.x4.shared.b16 {%0,%1,%2,%3}, [%4];"
                 : "=r"(r[0]), "=r"(r[1]), "=r"(r[2]), "=r"(r[3]) : "r"(addr) : "memory");
}
__device__ __forceinline__ void ldsm4t(uint32_t (&r)[4], uint32_t addr) {
    asm volatile("ldmatrix.sync.aligned.m8n8.x4.trans.shared.b16 {%0,%1,%2,%3}, [%4];"
                 : "=r"(r[0]), "=r"(r[1]), "=r"(r[2]), "=r"(r[3]) : "r"(addr) : "memory");
}
__device__ __forceinline__ void mma16816(float (&d)[4], const uint32_t (&a)[4], uint32_t b0, uint32_t b1) {
    asm volatile("mma.sync.aligned.m16n8k16.row.col.f32.bf16.bf16.f32 {%0,%1,%2,%3}, {%4,%5,%6,%7}, {%8,%9}, {%0,%1,%2,%3};"
                 : "+f"(d[0]), "+f"(d[1]), "+f"(d[2]), "+f"(d[3])
                 : "r"(a[0]), "r"(a[1]), "r"(a[2]), "r"(a[3]), "r"(b0), "r"(b1));
}
__device__ __forceinline__ uint32_t movtrans(uint32_t a) {
    uint32_t d;
    asm volatile("movmatrix.sync.aligned.m8n8.trans.b16 %0, %1;" : "=r"(d) : "r"(a));
    return d;
}
__device__ __forceinline__ uint32_t pack_bf16(float lo, float hi) {
    uint32_t d;
    asm("cvt.rn.bf16x2.f32 %0, %1, %2;" : "=r"(d) : "f"(hi), "f"(lo));
    return d;
}
__device__ __forceinline__ float bf16r(float x) { return __bfloat162float(__float2bfloat16_rn(x)); }
__device__ __forceinline__ float bf_lo(uint32_t u) { return __uint_as_float(u << 16); }
__device__ __forceinline__ float bf_hi(uint32_t u) { return __uint_as_float(u & 0xffff0000u); }
__device__ __forceinline__ uint32_t hadd2_bf16(uint32_t a, uint32_t b) {
    uint32_t d;
    asm("add.rn.bf16x2 %0, %1, %2;" : "=r"(d) : "r"(a), "r"(b));
    return d;
}
__device__ __forceinline__ uint32_t ld_rlx(const uint32_t* p) {
    uint32_t v; asm volatile("ld.relaxed.gpu.global.u32 %0, [%1];" : "=r"(v) : "l"(p) : "memory"); return v;
}
__device__ __forceinline__ void st_rlx(uint32_t* p, uint32_t v) {
    asm volatile("st.relaxed.gpu.global.u32 [%0], %1;" :: "l"(p), "r"(v) : "memory");
}
__device__ __forceinline__ uint4 ld_rlx_2x64(const void* p) {
    unsigned long long a, b;
    asm volatile("ld.relaxed.gpu.global.v2.b64 {%0,%1}, [%2];" : "=l"(a), "=l"(b) : "l"(p) : "memory");
    return make_uint4((uint32_t)a, (uint32_t)(a >> 32), (uint32_t)b, (uint32_t)(b >> 32));
}
__device__ __forceinline__ void reld_2x64(uint4& v, const void* p, uint32_t need) {
    asm volatile("{\n.reg .pred p;\n.reg .b64 a, b;\nsetp.ne.u32 p, %5, 0;\nmov.b64 a, {%0,%1};\nmov.b64 b, {%2,%3};\n"
                 "@p ld.relaxed.gpu.global.v2.b64 {a,b}, [%4];\nmov.b64 {%0,%1}, a;\nmov.b64 {%2,%3}, b;\n}"
                 : "+r"(v.x), "+r"(v.y), "+r"(v.z), "+r"(v.w) : "l"(p), "r"(need) : "memory");
}
__device__ __forceinline__ void st_rlx_2x64(void* p, const uint4& v) {
    asm volatile("st.relaxed.gpu.global.v2.b64 [%0], {%1,%2};" :: "l"(p),
                 "l"(((unsigned long long)v.y << 32) | v.x), "l"(((unsigned long long)v.w << 32) | v.z) : "memory");
}
__device__ __forceinline__ void st_rlx_64(void* p, uint32_t lo, uint32_t hi) {
    asm volatile("st.relaxed.gpu.global.b64 [%0], %1;" :: "l"(p), "l"(((unsigned long long)hi << 32) | lo) : "memory");
}
__device__ __forceinline__ bool tagged(const uint4& v, uint32_t tag) { return (((v.x ^ tag) | (v.z ^ tag)) & 1u) == 0u; }
__device__ __forceinline__ void sts128(uint32_t a, uint32_t x, uint32_t y, uint32_t z, uint32_t w) {
    asm volatile("st.shared.v4.b32 [%0], {%1,%2,%3,%4};" :: "r"(a), "r"(x), "r"(y), "r"(z), "r"(w) : "memory");
}
template <typename T> __device__ __forceinline__ void pin64(T*& p) { asm volatile("" : "+l"(p)); }
__device__ __forceinline__ void pin32(uint32_t& v) { asm volatile("" : "+r"(v)); }
__device__ __forceinline__ void cbar() { asm volatile("bar.sync 1, 256;" ::: "memory"); }
__device__ __forceinline__ float ex2(float x) { float y; asm("ex2.approx.ftz.f32 %0, %1;" : "=f"(y) : "f"(x)); return y; }

__global__ void __launch_bounds__(NTHREADS, 2)
fused_decode_kernel(const char* __restrict__ wq_raw, __nv_bfloat16* __restrict__ out, const __grid_constant__ Maps maps)
{
    extern __shared__ __align__(1024) char smp[];
    const uint32_t sm = smem_u32(smp);
    const int tid = threadIdx.x, warp = tid >> 5, lane = tid & 31;
    const int cta = blockIdx.x, g = cta >> 4, c = cta & 15, b = c >> 1, half = c & 1;
    const bool ffn = g < 7;
    const uint32_t bar_full = sm + OFF_BAR, bar_empty = bar_full + NCHUNK * 8;
    const uint32_t bar_q = bar_empty + 16 * 8, bar_ml = bar_q + 8, bar_r = bar_q + 16, bar_x = bar_q + 24, bar_go = bar_q + 32;
    const uint32_t bar_clk = bar_q + 40 - 13 * 8;

    if (warp == 8) {
        if (lane == 0) {
            mbar_init(bar_x, 1); mbar_init(bar_full, 1); mbar_init(bar_full + 8, 1); mbar_init(bar_full + 16, 1);
            asm volatile("fence.proxy.async.shared::cta;" ::: "memory");
            mbar_expect(bar_full, CHUNK); tma2d(sm, &maps.wq, cta * 32, 0, bar_full);
            mbar_expect(bar_x, 8192); tma3d(sm + OFF_X, &maps.x, 0, 0, 0, bar_x);
            mbar_expect(bar_full + 8, CHUNK); tma2d(sm + CHUNK, &maps.wq, cta * 32, 256, bar_full + 8);
            if (ffn) {
                mbar_expect(bar_full + 16, CHUNK);
                tma2d(sm + 2 * CHUNK, &maps.w1, cta * 16, 0, bar_full + 16);
                tma2d(sm + 2 * CHUNK + 8192, &maps.w1, cta * 16, 256, bar_full + 16);
            } else mbar_arrive(bar_full + 16);
            if (sm & 1023u) __trap();
            #pragma unroll
            for (int s = C_K; s < NCHUNK; s++) mbar_init(bar_full + s * 8, 1);
            #pragma unroll
            for (int s = 0; s < 16; s++) mbar_init(bar_empty + s * 8, (s < 2 || (s >= C_K && s < C_V)) ? 4 : 8);
            mbar_init(bar_q, 1); mbar_init(bar_ml, 1); mbar_init(bar_r, 1); mbar_init(bar_go, 1);
            #pragma unroll
            for (int s = 13; s < C_W2; s++) mbar_init(bar_clk + s * 8, clk_count(s));
            mbar_expect(bar_q, 1024); mbar_expect(bar_ml, 32); mbar_expect(bar_r, 4096);
            asm volatile("fence.mbarrier_init.release.cluster;" ::: "memory");
            asm volatile("fence.proxy.async.shared::cta;" ::: "memory");
        }
        __syncwarp();
        asm volatile("barrier.cluster.arrive.relaxed.aligned;" ::: "memory");
        asm volatile("bar.arrive 2, %0;" :: "n"(NTHREADS) : "memory");
        if (lane == 0) {
            const int row0 = (b * 8 + g) * 4096 + 3072 + half * 512;
            uint32_t dst = sm + C_K * CHUNK;
            #pragma unroll 1
            for (int ch = C_K; ch < NCHUNK; ch++) {
                if (ch >= 17) mbar_wait(bar_clk + (ch < C_W2 ? ch - 4 : ch - 3) * 8);
                else if (ch >= DEPTH) mbar_wait(bar_full + (ch - DEPTH) * 8);
                if (ch >= NSLOT) mbar_wait(bar_empty + (ch - NSLOT) * 8);
                const uint32_t bar = bar_full + ch * 8;
                if (ch < C_W2) {
                    mbar_expect(bar, CHUNK);
                    tma3d(dst, ch < C_V ? &maps.k : &maps.v, 0, row0 + ((ch - C_K) & 7) * 64, 0, bar);
                } else {
                    mbar_expect(bar, ch == C_W2 ? 14336 : CHUNK);
                    tma2d(dst, ch == C_W2 ? &maps.w2 : &maps.wo, g * 64,
                          ch == C_W2 ? c * 112 : c * 256 + (ch - C_WO) * 128, bar);
                }
                dst = (dst == sm + (NSLOT - 1) * CHUNK) ? sm : dst + CHUNK;
            }
            mbar_wait(bar_clk + 15 * 8);
            mbar_arrive(bar_go);
            #pragma unroll
            for (int s = 13; s < C_W2; s++)
                asm volatile("mbarrier.arrive.shared::cta.b64 _, [%0], %1;" :: "r"(bar_clk + s * 8), "r"(2 * clk_count(s) - 16) : "memory");
            #pragma unroll
            for (int s = 13; s < C_W2; s++)
                for (uint32_t n = 0; !mbar_try<1>(bar_clk + s * 8); ) if (++n > BAR_LIMIT) __trap();
        }
        __syncwarp();
        asm volatile("barrier.cluster.wait.aligned;" ::: "memory");
        return;
    }

    if (tid == 0) l2_prefetch(wq_raw + (size_t)cta * 32768, PF_BYTES);
    asm volatile("barrier.cluster.arrive.relaxed.aligned;" ::: "memory");
    const int gl = lane >> 2, t = lane & 3;
    float* lnst = reinterpret_cast<float*>(smp + OFF_STAT + 256);
    volatile uint32_t* epoch_s = reinterpret_cast<volatile uint32_t*>(smp + OFF_STAT + 320);
    const int ru = lane & 7, rp = lane >> 3;
    const int ob = 2 * (ru & 3) + (rp & 1);
    const int ocol = g * 64 + (c >> 2) * 16 + 2 * (c & 3) + (ru >> 2) + 8 * (rp >> 1);
    uint32_t epoch_r = 0;
    if (tid == 64) epoch_r = ld_rlx(&g_epoch);
    asm volatile("bar.sync 2, %0;" :: "n"(NTHREADS) : "memory");
    if (tid == 64) *epoch_s = epoch_r;
    mbar_wait(bar_x);
    uint32_t xf[8];
    #pragma unroll
    for (int j = 0; j < 8; j++)
        xf[j] = *reinterpret_cast<const uint32_t*>(smp + OFF_X + warp * 1024 + gl * 128 + ((j ^ gl) << 4) + t * 4);
    const float resid = __bfloat162float(*reinterpret_cast<const __nv_bfloat16*>(
        smp + OFF_X + g * 1024 + ob * 128 + ((((ocol >> 3) & 7) ^ ob) << 4) + (ocol & 7) * 2));
    {
        const char* xr = smp + OFF_X + (lane >> 3) * 1024 + warp * 128 + (lane & 7) * 16;
        const uint4 xa = *reinterpret_cast<const uint4*>(xr), xb = *reinterpret_cast<const uint4*>(xr + 4096);
        const float sh = bf_lo(*reinterpret_cast<const uint32_t*>(smp + OFF_X + warp * 128));
        const uint32_t w[8] = {xa.x, xa.y, xa.z, xa.w, xb.x, xb.y, xb.z, xb.w};
        float s4[4] = {}, q4[4] = {};
        #pragma unroll
        for (int j = 0; j < 8; j++) {
            const float lo = bf_lo(w[j]) - sh, hi = bf_hi(w[j]) - sh;
            s4[j & 3] += lo + hi;
            q4[j & 3] = fmaf(lo, lo, fmaf(hi, hi, q4[j & 3]));
        }
        float s = (s4[0] + s4[1]) + (s4[2] + s4[3]), q2 = (q4[0] + q4[1]) + (q4[2] + q4[3]);
        #pragma unroll
        for (int o = 16; o > 0; o >>= 1) {
            s += __shfl_xor_sync(0xffffffffu, s, o);
            q2 += __shfl_xor_sync(0xffffffffu, q2, o);
        }
        const float ms = s * (1.f / 512.f), mean = sh + ms;
        q2 = fmaxf(fmaf(-ms, s, q2), 0.f);
        const float den = bf16r(__fsqrt_rn(bf16r(bf16r(q2 * (1.f / 512.f)) + 1e-5f)));
        if (lane == 0) *reinterpret_cast<float2*>(lnst + warp * 2) = make_float2(bf16r(mean), __frcp_rn(den));
    }
    cbar();
    {
        const float2 st = *reinterpret_cast<const float2*>(lnst + gl * 2);
        #pragma unroll
        for (int j = 0; j < 8; j++)
            xf[j] = pack_bf16(bf16r(bf_lo(xf[j]) - st.x) * st.y, bf16r(bf_hi(xf[j]) - st.x) * st.y);
    }
    const uint32_t tag = (*epoch_s + 1u) & 1u;

    float* red = reinterpret_cast<float*>(smp + OFF_RED);
    const int mj = lane >> 3, mr = lane & 7;
    float* r0 = red + (warp * 8 + 2 * t) * RED_PITCH + gl;
    {
        float aq[2][4] = {};
        mbar_wait(bar_full + (warp >> 2) * 8);
        const uint32_t wqs = sm + (warp >> 2) * CHUNK;
        #pragma unroll
        for (int s = 0; s < 4; s++) {
            const int row = (warp & 3) * 64 + s * 16 + (mj >> 1) * 8 + mr;
            #pragma unroll
            for (int j = 0; j < 2; j++) {
                uint32_t a[4];
                ldsm4t(a, wqs + row * 64 + (((2 * j + (mj & 1)) ^ ((row >> 1) & 3)) << 4));
                mma16816(aq[j], a, xf[2 * s], xf[2 * s + 1]);
            }
        }
        __syncwarp();
        if (lane == 0) mbar_arrive(bar_empty + (warp >> 2) * 8);
        #pragma unroll
        for (int j = 0; j < 2; j++) {
            r0[j * 16] = aq[j][0]; r0[RED_PITCH + j * 16] = aq[j][1];
            r0[j * 16 + 8] = aq[j][2]; r0[RED_PITCH + j * 16 + 8] = aq[j][3];
        }
    }
    cbar();
    asm volatile("barrier.cluster.wait.aligned;" ::: "memory");
    if (warp < 4) {
        const int bb = tid >> 4, wd = tid & 15;
        const int col = (wd >> 3) * 16 + ((wd >> 1) & 3) * 2 + (wd & 1) * 8;
        float s0 = 0.f, s1 = 0.f;
        #pragma unroll
        for (int w = 0; w < 8; w++) {
            const float2 f = *reinterpret_cast<const float2*>(red + (w * 8 + bb) * RED_PITCH + col);
            s0 += f.x; s1 += f.y;
        }
        const uint32_t u = pack_bf16(s0, s1);
        const int q0 = (lane & 16) + (lane & 3) * 4;
        const uint32_t u0 = __shfl_sync(0xffffffffu, u, q0), u1 = __shfl_sync(0xffffffffu, u, q0 + 1);
        const uint32_t u2 = __shfl_sync(0xffffffffu, u, q0 + 2), u3 = __shfl_sync(0xffffffffu, u, q0 + 3);
        if (wd < 8) {
            const uint32_t rank = 2 * bb + (wd >> 2);
            st_async4(mapa(sm + OFF_Q + c * 64 + (wd & 3) * 16, rank), u0, u1, u2, u3, mapa(bar_q, rank));
        }
    }
    if (ffn) {
        float ah[4] = {};
        mbar_wait(bar_full + 2 * 8);
        const uint32_t w1s = sm + 2 * CHUNK;
        #pragma unroll
        for (int s = 0; s < 4; s++) {
            const int row = warp * 64 + s * 16 + (mj >> 1) * 8 + mr;
            uint32_t a[4];
            ldsm4t(a, w1s + row * 32 + (((mj & 1) ^ ((row >> 2) & 1)) << 4));
            mma16816(ah, a, xf[2 * s], xf[2 * s + 1]);
        }
        __syncwarp();
        if (lane == 0) mbar_arrive(bar_empty + 2 * 8);
        cbar();
        r0[0] = ah[0]; r0[RED_PITCH] = ah[1]; r0[8] = ah[2]; r0[RED_PITCH + 8] = ah[3];
        cbar();
        if (warp >= 6) {
            const int bb = (tid & 63) >> 3, wd = tid & 7;
            float s0 = 0.f, s1 = 0.f;
            #pragma unroll
            for (int w = 0; w < 8; w++) {
                const float2 f = *reinterpret_cast<const float2*>(red + (w * 8 + bb) * RED_PITCH + 2 * wd);
                s0 += f.x; s1 += f.y;
            }
            s0 = bf16r(s0); s1 = bf16r(s1);
            s0 = __fdividef(s0, 1.f + __expf(-s0)); s1 = __fdividef(s1, 1.f + __expf(-s1));
            st_rlx_64(g_h + (bb * 896 + cta * 8 + wd) * 2, tag, pack_bf16(s0, s1));
        }
    } else {
        __syncwarp();
        if (lane == 0) mbar_arrive(bar_empty + 2 * 8);
    }

    float sc[4][4];
    float m0 = -INFINITY, m1 = -INFINITY;
    {
        mbar_wait_cluster(bar_q);
        uint32_t qb[8][2];
        #pragma unroll
        for (int s = 0; s < 8; s++) {
            const uint2 v = *reinterpret_cast<const uint2*>(smp + OFF_Q + (((gl & 3) * 8 + s) * 4 + t) * 8);
            qb[s][0] = v.x; qb[s][1] = v.y;
        }
        const uint32_t koff = ((warp & 3) * 16 + (mj & 1) * 8 + mr) * 128;
        #pragma unroll
        for (int i = 0; i < 4; i++) {
            const int ck = C_K + 2 * i + (warp >> 2);
            mbar_wait(bar_full + ck * 8);
            const uint32_t ks = sm + (ck % NSLOT) * CHUNK + koff;
            float s0[4] = {}, s1[4] = {};
            #pragma unroll
            for (int s = 0; s < 4; s++) {
                const uint32_t sw = ((2 * s + (mj >> 1)) ^ mr) << 4;
                uint32_t a[4], a2[4];
                ldsm4(a, ks + sw);
                ldsm4(a2, ks + 8192 + sw);
                mma16816(s0, a, qb[s][0], qb[s][1]);
                mma16816(s1, a2, qb[4 + s][0], qb[4 + s][1]);
            }
            __syncwarp();
            if (lane == 0) mbar_arrive(bar_empty + ck * 8);
            #pragma unroll
            for (int k = 0; k < 4; k++) sc[i][k] = bf16r(bf16r(s0[k] + s1[k]) * 0.08838834764831845f);
            m0 = fmaxf(m0, fmaxf(sc[i][0], sc[i][2]));
            m1 = fmaxf(m1, fmaxf(sc[i][1], sc[i][3]));
        }
    }
    float* wmax = reinterpret_cast<float*>(smp + OFF_STAT);
    float* wsum = wmax + 32;
    constexpr float L2E = 1.4426950408889634f;
    {
        #pragma unroll
        for (int o = 4; o < 32; o <<= 1) {
            m0 = fmaxf(m0, __shfl_xor_sync(0xffffffffu, m0, o));
            m1 = fmaxf(m1, __shfl_xor_sync(0xffffffffu, m1, o));
        }
        if (lane < 2) *reinterpret_cast<float2*>(wmax + warp * 4 + 2 * lane) = make_float2(m0, m1);
        cbar();
        #pragma unroll
        for (int w = 0; w < 8; w++) {
            const float2 f = *reinterpret_cast<const float2*>(wmax + w * 4 + 2 * (t & 1));
            m0 = fmaxf(m0, f.x); m1 = fmaxf(m1, f.y);
        }
        float l0 = 0.f, l1 = 0.f;
        uint32_t pw[4][2];
        #pragma unroll
        for (int i = 0; i < 4; i++) {
            const float p0 = ex2((sc[i][0] - m0) * L2E), p1 = ex2((sc[i][1] - m1) * L2E);
            const float p2 = ex2((sc[i][2] - m0) * L2E), p3 = ex2((sc[i][3] - m1) * L2E);
            l0 += p0 + p2; l1 += p1 + p3;
            pw[i][0] = movtrans(pack_bf16(p0, p1));
            pw[i][1] = movtrans(pack_bf16(p2, p3));
        }
        if (lane < 16) {
            char* pd = smp + OFF_P + ((warp >> 2) * 2 + ((warp >> 1) & 1)) * 256 + lane * 16 + (warp & 1) * 8;
            #pragma unroll
            for (int i = 0; i < 4; i++) *reinterpret_cast<uint2*>(pd + i * 1024) = make_uint2(pw[i][0], pw[i][1]);
        }
        #pragma unroll
        for (int o = 4; o < 32; o <<= 1) {
            l0 += __shfl_xor_sync(0xffffffffu, l0, o);
            l1 += __shfl_xor_sync(0xffffffffu, l1, o);
        }
        if (lane < 2) *reinterpret_cast<float2*>(wsum + warp * 4 + 2 * lane) = make_float2(l0, l1);
    }
    cbar();
    float l0 = 0.f, l1 = 0.f;
    #pragma unroll
    for (int w = 0; w < 8; w++) {
        const float2 f = *reinterpret_cast<const float2*>(wsum + w * 4 + 2 * (t & 1));
        l0 += f.x; l1 += f.y;
    }
    if (tid < 2) {
        const uint32_t dst = mapa(sm + OFF_ML + tid * 8, c ^ 1), bar = mapa(bar_ml, c ^ 1);
        st_async2(dst, __float_as_uint(m0), __float_as_uint(m1), bar);
        st_async2(dst + 16, __float_as_uint(l0), __float_as_uint(l1), bar);
    }

    const uint32_t* op = g_o + (((tid >> 4) & 7) * 32 + 2 * c + (tid >> 7)) * 64 + (tid & 15) * 4;
    uint32_t* opub = g_o + ((half * 8 + b) * 32 + g * 4) * 64 + (tid & 63) * 4;
    __nv_bfloat16* outp = out + ob * 512 + ocol;
    uint32_t s_ost = sm + OFF_OST + gl * 256 + (t * 4 + ((warp >> 1) ^ (t & 2))) * 16 + (warp & 1) * 8;
    uint32_t s_rdst = mapa(sm + OFF_RIN + (c * 2 + (warp >> 2)) * 128 + ru * 16, (warp & 3) * 4 + rp);
    uint32_t s_rbar = mapa(bar_r, (warp & 3) * 4 + rp);
    uint32_t s_obw = sm + OFF_OB + (tid >> 4) * 320 + (((tid & 15) ^ ((tid >> 4) & 1)) << 4);
    uint32_t s_obr = sm + OFF_OB + gl * 320 + t * 64 + ((((warp >> 2) * 2) ^ (t & 2) ^ (gl & 1)) << 4);
    const int hb = min(tid / 28, 7), hpc = tid - (tid / 28) * 28;
    const uint32_t* hp = g_h + (hb * 896 + c * 56 + hpc * 2) * 2;
    uint32_t s_h = sm + OFF_H + hb * 272 + hpc * 8;
    pin64(op); pin64(opub); pin64(outp); pin64(hp);
    uint32_t aoff = sm + (warp >> 2) * 8192 + ((mj >> 1) * 8 + mr) * 128 + (((2 * (warp & 3) + (mj & 1)) ^ mr) << 4);
    uint32_t s_hs = sm + OFF_H + (gl * 68 + (warp >> 2) * 32 + t) * 4;
    uint32_t s_rin = sm + OFF_RIN + lane * 16;
    uint32_t ptid = tid;
    uint32_t s_clk = mapa(bar_clk + C_V * 8, tid & 15);
    pin32(s_ost); pin32(s_rdst); pin32(s_rbar); pin32(s_obw); pin32(s_obr); pin32(s_h);
    pin32(aoff); pin32(s_hs); pin32(s_rin); pin32(ptid); pin32(s_clk);
    uint4 hv = make_uint4(tag, 0u, tag, 0u);
    if (tid < 224) hv = ld_rlx_2x64(hp);
    if (tid < 64) st_rlx_2x64(opub, make_uint4(tag ^ 1u, 0u, tag ^ 1u, 0u));

    float f0 = 0.f, f1 = 0.f;
    float oc[4][4] = {};
    {
        const int ach = 2 * warp + (mj & 1);
        uint32_t voff = (ach >> 3) * 8192 + ((mj >> 1) * 8 + mr) * 128 + (((ach & 7) ^ mr) << 4);
        pin32(voff);
        const uint4* pfp = reinterpret_cast<const uint4*>(smp + OFF_P) + (lane & 15);
        uint32_t vs = sm + (C_V % NSLOT) * CHUNK;
        #pragma unroll 1
        for (int j = 0; j < 8; j++) {
            const uint4 pa = pfp[j * 32], pb = pfp[j * 32 + 16];
            if (j == 6) {
                for (uint32_t n = 0; !tagged(hv, tag); ) {
                    hv = ld_rlx_2x64(hp);
                    if (++n > POLL_LIMIT) __trap();
                }
                if (tid < 224) asm volatile("st.shared.v2.b32 [%0], {%1,%2};" :: "r"(s_h), "r"(hv.y), "r"(hv.w) : "memory");
                __syncwarp();
                mbar_wait_cluster(bar_ml);
                const float* pm = reinterpret_cast<const float*>(smp + OFF_ML) + (t & 1) * 2;
                const float mo0 = pm[0], mo1 = pm[1];
                const float mt0 = fmaxf(m0, mo0), mt1 = fmaxf(m1, mo1);
                const float e0 = ex2((m0 - mt0) * L2E), e1 = ex2((m1 - mt1) * L2E);
                f0 = __fdividef(e0, l0 * e0 + pm[4] * ex2((mo0 - mt0) * L2E));
                f1 = __fdividef(e1, l1 * e1 + pm[5] * ex2((mo1 - mt1) * L2E));
            }
            mbar_wait(bar_full + (C_V + j) * 8);
            if (j >= 2 && j != 4 && ptid >= 240) tick_remote(s_clk + j * 8);
            uint32_t a[4][4];
            #pragma unroll
            for (int s = 0; s < 4; s++) ldsm4t(a[s], vs + voff + s * 2048);
            mma16816(oc[0], a[0], pa.x, pa.y);
            mma16816(oc[1], a[1], pa.z, pa.w);
            mma16816(oc[2], a[2], pb.x, pb.y);
            mma16816(oc[3], a[3], pb.z, pb.w);
            __syncwarp();
            if (j < 5 && lane == 0) mbar_arrive(bar_empty + (C_V + j) * 8);
            vs = (vs == sm + (NSLOT - 1) * CHUNK) ? sm : vs + CHUNK;
        }
    }
    {
        const float o0 = (oc[0][0] + oc[1][0]) + (oc[2][0] + oc[3][0]);
        const float o1 = (oc[0][1] + oc[1][1]) + (oc[2][1] + oc[3][1]);
        const float o2 = (oc[0][2] + oc[1][2]) + (oc[2][2] + oc[3][2]);
        const float o3 = (oc[0][3] + oc[1][3]) + (oc[2][3] + oc[3][3]);
        const uint32_t u0 = movtrans(pack_bf16(o0 * f0, o1 * f1));
        const uint32_t u1 = movtrans(pack_bf16(o2 * f0, o3 * f1));
        if (!(ptid & 16))
            asm volatile("st.shared.v2.b32 [%0], {%1,%2};" :: "r"(s_ost), "r"((u0 & ~1u) | tag), "r"(u1) : "memory");
        cbar();
        if (ptid < 64) st_rlx_2x64(opub, *reinterpret_cast<const uint4*>(smp + OFF_OST + ptid * 16));
        if (ptid >= 240) tick_remote(s_clk + 4 * 8);
    }

    {
        float ac[4][4] = {};
        mbar_wait(bar_full + C_W2 * 8);
        #pragma unroll
        for (int s = 0; s < 4; s++) {
            if (s < 3 || ptid < 128) {
                uint32_t a[4], h0, h1;
                ldsm4t(a, aoff + (C_W2 % NSLOT) * CHUNK + s * 2048);
                asm volatile("ld.shared.b32 %0, [%1];" : "=r"(h0) : "r"(s_hs + s * 32) : "memory");
                asm volatile("ld.shared.b32 %0, [%1];" : "=r"(h1) : "r"(s_hs + s * 32 + 16) : "memory");
                mma16816(ac[s], a, h0, h1);
            }
        }
        mbar_wait(bar_go);
        uint4 oa = ld_rlx_2x64(op), obv = ld_rlx_2x64(op + 16384);
        uint32_t wa[8][4];
        bool have0 = false, have1 = false;
        auto wo_part = [&](int i) {
            #pragma unroll
            for (int s = 0; s < 4; s++) ldsm4t(wa[i * 4 + s], aoff + (C_WO % NSLOT + i) * CHUNK + s * 2048);
        };
        uint32_t ax, az, bx, bz;
        for (uint32_t n = 0; ; ) {
            if (!have0 && __all_sync(0xffffffffu, mbar_test(bar_full + C_WO * 8))) { have0 = true; wo_part(0); }
            if (!have1 && __all_sync(0xffffffffu, mbar_test(bar_full + (C_WO + 1) * 8))) { have1 = true; wo_part(1); }
            if (++n > POLL_LIMIT) __trap();
            ax = oa.x ^ tag; az = oa.z ^ tag; bx = obv.x ^ tag; bz = obv.z ^ tag;
            const uint32_t na = (ax | az) & 1u, nb = (bx | bz) & 1u;
            if (!__any_sync(0xffffffffu, na | nb)) break;
            reld_2x64(oa, op, na);
            reld_2x64(obv, op + 16384, nb);
        }
        sts128(s_obw, hadd2_bf16(ax, bx), hadd2_bf16(oa.y, obv.y), hadd2_bf16(az, bz), hadd2_bf16(oa.w, obv.w));
        cbar();
        uint4 of[4];
        #pragma unroll
        for (int i = 0; i < 4; i++)
            asm volatile("ld.shared.v4.b32 {%0,%1,%2,%3}, [%4];" : "=r"(of[i].x), "=r"(of[i].y), "=r"(of[i].z), "=r"(of[i].w)
                         : "r"((s_obr ^ ((i & 1) << 4)) + (i >> 1) * 2560) : "memory");
        if (!have0) { mbar_wait(bar_full + C_WO * 8); wo_part(0); }
        mma16816(ac[0], wa[0], of[0].x, of[0].y);
        mma16816(ac[1], wa[1], of[0].z, of[0].w);
        mma16816(ac[2], wa[2], of[1].x, of[1].y);
        mma16816(ac[3], wa[3], of[1].z, of[1].w);
        if (!have1) { mbar_wait(bar_full + (C_WO + 1) * 8); wo_part(1); }
        mma16816(ac[0], wa[4], of[2].x, of[2].y);
        mma16816(ac[1], wa[5], of[2].z, of[2].w);
        mma16816(ac[2], wa[6], of[3].x, of[3].y);
        mma16816(ac[3], wa[7], of[3].z, of[3].w);
        st_async4(s_rdst,
                  __float_as_uint((ac[0][0] + ac[1][0]) + (ac[2][0] + ac[3][0])),
                  __float_as_uint((ac[0][1] + ac[1][1]) + (ac[2][1] + ac[3][1])),
                  __float_as_uint((ac[0][2] + ac[1][2]) + (ac[2][2] + ac[3][2])),
                  __float_as_uint((ac[0][3] + ac[1][3]) + (ac[2][3] + ac[3][3])), s_rbar);
    }

    if (ptid < 32) {
        mbar_wait_cluster(bar_r);
        float4 v[8];
        #pragma unroll
        for (int i = 0; i < 8; i++)
            asm volatile("ld.shared.v4.f32 {%0,%1,%2,%3}, [%4];" : "=f"(v[i].x), "=f"(v[i].y), "=f"(v[i].z), "=f"(v[i].w)
                         : "r"(s_rin + i * 512) : "memory");
        const float s0 = ((v[0].x + v[1].x) + (v[2].x + v[3].x)) + ((v[4].x + v[5].x) + (v[6].x + v[7].x));
        const float s1 = ((v[0].y + v[1].y) + (v[2].y + v[3].y)) + ((v[4].y + v[5].y) + (v[6].y + v[7].y));
        const float s2 = ((v[0].z + v[1].z) + (v[2].z + v[3].z)) + ((v[4].z + v[5].z) + (v[6].z + v[7].z));
        const float s3 = ((v[0].w + v[1].w) + (v[2].w + v[3].w)) + ((v[4].w + v[5].w) + (v[6].w + v[7].w));
        const bool p1 = ptid & 8, p2 = ptid & 16;
        float a = p1 ? s1 : s0, bq = p1 ? s3 : s2;
        a += __shfl_xor_sync(0xffffffffu, p1 ? s0 : s1, 8);
        bq += __shfl_xor_sync(0xffffffffu, p1 ? s2 : s3, 8);
        float r = p2 ? bq : a;
        r += __shfl_xor_sync(0xffffffffu, p2 ? a : bq, 16);
        *outp = __float2bfloat16_rn(r + resid);
        if (cta == 0 && lane == 0) st_rlx(&g_epoch, *epoch_s + 1u);
    }
}

typedef CUresult (*EncodeFn)(CUtensorMap*, CUtensorMapDataType, cuuint32_t, void*, const cuuint64_t*, const cuuint64_t*,
                             const cuuint32_t*, const cuuint32_t*, CUtensorMapInterleave, CUtensorMapSwizzle,
                             CUtensorMapL2promotion, CUtensorMapFloatOOBfill);

void encode(EncodeFn fn, CUtensorMap* m, const void* p, int rank, const cuuint64_t* dims, const cuuint64_t* strides,
            const cuuint32_t* box, CUtensorMapSwizzle sw,
            CUtensorMapL2promotion promo = CU_TENSOR_MAP_L2_PROMOTION_L2_256B) {
    const cuuint32_t es[3] = {1, 1, 1};
    fn(m, CU_TENSOR_MAP_DATA_TYPE_BFLOAT16, rank, const_cast<void*>(p), dims, strides, box, es,
       CU_TENSOR_MAP_INTERLEAVE_NONE, sw, promo, CU_TENSOR_MAP_FLOAT_OOB_FILL_NONE);
}

}

extern "C" void kernel_launch(void* const* d_in, const int* in_sizes, int n_in, void* d_out, int out_size) {
    (void)in_sizes; (void)n_in; (void)out_size;
    static EncodeFn fn = nullptr;
    if (!fn) {
        cudaDriverEntryPointQueryResult qr;
        cudaGetDriverEntryPoint("cuTensorMapEncodeTiled", (void**)&fn, cudaEnableDefault, &qr);
        cudaFuncSetAttribute(fused_decode_kernel, cudaFuncAttributeMaxDynamicSharedMemorySize, SMEM_BYTES);
        cudaFuncSetAttribute(fused_decode_kernel, cudaFuncAttributeNonPortableClusterSizeAllowed, 1);
    }
    Maps m;
    {
        const cuuint64_t d[3] = {64, 64ull * 4096, 2}, s[2] = {256, 128};
        const cuuint32_t bx[3] = {64, 64, 2};
        encode(fn, &m.k, d_in[1], 3, d, s, bx, CU_TENSOR_MAP_SWIZZLE_128B);
        encode(fn, &m.v, d_in[2], 3, d, s, bx, CU_TENSOR_MAP_SWIZZLE_128B);
    }
    { const cuuint64_t d[3] = {64, 8, 8}, s[2] = {1024, 128}; const cuuint32_t bx[3] = {64, 8, 8};
      encode(fn, &m.x, d_in[0], 3, d, s, bx, CU_TENSOR_MAP_SWIZZLE_128B); }
    { const cuuint64_t d[2] = {4096, 512}, s[1] = {8192}; const cuuint32_t bx[2] = {32, 256};
      encode(fn, &m.wq, d_in[3], 2, d, s, bx, CU_TENSOR_MAP_SWIZZLE_64B); }
    { const cuuint64_t d[2] = {512, 4096}, s[1] = {1024}; const cuuint32_t bx[2] = {64, 128};
      encode(fn, &m.wo, d_in[4], 2, d, s, bx, CU_TENSOR_MAP_SWIZZLE_128B, CU_TENSOR_MAP_L2_PROMOTION_L2_128B); }
    { const cuuint64_t d[2] = {1792, 512}, s[1] = {3584}; const cuuint32_t bx[2] = {16, 256};
      encode(fn, &m.w1, d_in[6], 2, d, s, bx, CU_TENSOR_MAP_SWIZZLE_32B); }
    { const cuuint64_t d[2] = {512, 1792}, s[1] = {1024}; const cuuint32_t bx[2] = {64, 112};
      encode(fn, &m.w2, d_in[7], 2, d, s, bx, CU_TENSOR_MAP_SWIZZLE_128B, CU_TENSOR_MAP_L2_PROMOTION_L2_128B); }

    cudaLaunchConfig_t cfg = {};
    cfg.gridDim = dim3(NCTA); cfg.blockDim = dim3(NTHREADS); cfg.dynamicSmemBytes = SMEM_BYTES;
    cfg.stream = cudaStreamPerThread;
    cudaLaunchAttribute at[2];
    at[0].id = cudaLaunchAttributeClusterDimension;
    at[0].val.clusterDim.x = CLUSTER; at[0].val.clusterDim.y = 1; at[0].val.clusterDim.z = 1;
    at[1].id = cudaLaunchAttributeClusterSchedulingPolicyPreference;
    at[1].val.clusterSchedulingPolicyPreference = cudaClusterSchedulingPolicyLoadBalancing;
    cfg.attrs = at; cfg.numAttrs = 2;
    cudaLaunchKernelEx(&cfg, fused_decode_kernel, (const char*)d_in[3], (__nv_bfloat16*)d_out, m);
}
```
